```python
import torch

def _softmax(x, axis=-1):
    return torch.softmax(x, dim=axis)
def _gelu(x):
    return torch.nn.functional.gelu(x, approximate="tanh")
def _silu(x):
    return torch.nn.functional.silu(x)
def _sigmoid(x):
    return torch.sigmoid(x)
def _layernorm(x, axis=-1, eps=1e-5):
    m = x.mean(dim=axis, keepdim=True)
    v = x.var(dim=axis, keepdim=True, unbiased=False)
    return (x - m) / torch.sqrt(v + eps)
def _scatter_add(tgt, idx, src, axis=0):
    return tgt.clone().index_add_(axis, idx, src)
def _segment_sum(src, seg, n):
    out = torch.zeros((n,) + src.shape[1:], dtype=src.dtype)
    return out.index_add_(0, seg, src)
def _pad(x, pw):
    flat = tuple(v for pair in reversed(pw) for v in pair)
    return torch.nn.functional.pad(x, flat)

kernel_name = 'recurrent_scan__softmax_full_mha__glu_gated_bilinear__prompt'

def setup_inputs():

    _w = (lambda a: (lambda t: t.to(torch.bfloat16) if t.is_floating_point() else t)(torch.as_tensor(a)))
    def _A_setup():
        B, S, D = 1, 2048, 512
        return {
            "x": _w((lambda *s: torch.randn(*s, dtype=torch.bfloat16) * 0.05)(B, S, D)),
            "wqkv": _w((lambda *s: torch.randn(*s, dtype=torch.bfloat16) * 0.2)(D, 3 * D)),
            "wo": _w((lambda *s: torch.randn(*s, dtype=torch.bfloat16) * 0.2)(D, D)),
        }
    _A_in = _A_setup()

    def _B_setup():
        B, S, D, F = 1, 2048, 512, 1792
        return {
            "x": _w((lambda *s: torch.randn(*s, dtype=torch.bfloat16) * 0.05)(B, S, D)),
            "w_gate": _w((lambda *s: torch.randn(*s, dtype=torch.bfloat16) * 0.1)(D, F) * (D ** -0.5)),
            "w_up": _w((lambda *s: torch.randn(*s, dtype=torch.bfloat16) * 0.1)(D, F) * (D ** -0.5)),
            "w_down": _w((lambda *s: torch.randn(*s, dtype=torch.bfloat16) * 0.1)(F, D) * (F ** -0.5)),
        }
    _B_in = _B_setup()

    return {
        "A_x": _A_in["x"],
        "A_wqkv": _A_in["wqkv"],
        "A_wo": _A_in["wo"],
        "B_x": _B_in["x"],
        "B_w_gate": _B_in["w_gate"],
        "B_w_up": _B_in["w_up"],
        "B_w_down": _B_in["w_down"],
    }

def reference(A_x, A_wqkv, A_wo, B_x, B_w_gate, B_w_up, B_w_down):
    def _A_ref(x, wqkv, wo):
        B, S, D = x.shape
        H = 32; Dh = D // H
        qkv = (lambda x, *d: x.permute(*d))((x @ wqkv).reshape(B, S, 3, H, Dh), 2, 0, 3, 1, 4)
        q, k, v = qkv[0], qkv[1], qkv[2]
        scale = Dh ** -0.5
        scores = torch.einsum("bhqd,bhkd->bhqk", q, k) * scale
        p = _softmax(scores, axis=-1)
        o = torch.einsum("bhqk,bhkd->bhqd", p, v)
        return (lambda x, *d: x.permute(*d))(o, 0, 2, 1, 3).reshape(B, S, D) @ wo

    def _B_ref(x, w_gate, w_up, w_down):
        g = torch.einsum("bsd,df->bsf", x, w_gate)
        u = torch.einsum("bsd,df->bsf", x, w_up)
        h = g * u
        return torch.einsum("bsf,fd->bsd", h, w_down)

    x = A_x
    xn = _layernorm(x, axis=-1)
    s = _A_ref(xn, A_wqkv, A_wo)
    g = _silu(_B_ref(xn, B_w_gate, B_w_up, B_w_down))
    return x + s * g
```

```cpp
#include <cuda_runtime.h>
#include <cuda_bf16.h>
#include <cuda.h>
#include <stdint.h>

namespace {

constexpr int S = 2048, D = 512, H = 32, F = 1792;

__device__ __align__(1024) uint4 g_qkv[3 * H * 2 * S];
__device__ __align__(1024) __nv_bfloat16 g_xn[S * D];
__device__ __align__(1024) __nv_bfloat16 g_h[S * F];
__device__ __align__(1024) __nv_bfloat16 g_o[S * D];
__device__ __align__(1024) __nv_bfloat16 g_g[S * D];
__device__ unsigned g_flag[16];

__device__ __forceinline__ uint32_t smem_u32(const void* p) { return (uint32_t)__cvta_generic_to_shared(p); }
__device__ __forceinline__ void mbar_init(uint32_t b, uint32_t n) { asm volatile("mbarrier.init.shared::cta.b64 [%0], %1;" ::"r"(b), "r"(n)); }
__device__ __forceinline__ void mbar_expect(uint32_t b, uint32_t bytes) { asm volatile("mbarrier.arrive.expect_tx.shared::cta.b64 _, [%0], %1;" ::"r"(b), "r"(bytes) : "memory"); }
__device__ __forceinline__ void mbar_arrive(uint32_t b) { asm volatile("mbarrier.arrive.shared::cta.b64 _, [%0];" ::"r"(b) : "memory"); }
__device__ __forceinline__ void mbar_wait(uint32_t b, uint32_t parity) {
    uint32_t ok;
    int spin = 0;
    do {
        asm volatile("{ .reg .pred p; mbarrier.try_wait.parity.shared::cta.b64 p, [%1], %2; selp.b32 %0, 1, 0, p; }" : "=r"(ok) : "r"(b), "r"(parity) : "memory");
    } while (!ok && ++spin < (1 << 24));
    if (!ok) __trap();
}
__device__ __forceinline__ void fence_async_smem() { asm volatile("fence.proxy.async.shared::cta;" ::: "memory"); }
__device__ __forceinline__ void fence_bar_init() { asm volatile("fence.mbarrier_init.release.cluster;" ::: "memory"); }
__device__ __forceinline__ void named_bar(int id, int n) { asm volatile("bar.sync %0, %1;" ::"r"(id), "r"(n) : "memory"); }
__device__ __forceinline__ void pdl_wait() { asm volatile("griddepcontrol.wait;" ::: "memory"); }
__device__ __forceinline__ void pdl_launch() { asm volatile("griddepcontrol.launch_dependents;" ::: "memory"); }
__device__ __forceinline__ void tma_load(uint32_t dst, const CUtensorMap* m, int c0, int c1, uint32_t bar) {
    asm volatile("cp.async.bulk.tensor.2d.shared::cluster.global.mbarrier::complete_tx::bytes [%0], [%1, {%3, %4}], [%2];"
                 ::"r"(dst), "l"(m), "r"(bar), "r"(c0), "r"(c1) : "memory");
}
__device__ __forceinline__ void tma_store(const CUtensorMap* m, int c0, int c1, uint32_t src) {
    asm volatile("cp.async.bulk.tensor.2d.global.shared::cta.bulk_group [%0, {%2, %3}], [%1];" ::"l"(m), "r"(src), "r"(c0), "r"(c1) : "memory");
    asm volatile("cp.async.bulk.commit_group;" ::: "memory");
}
__device__ __forceinline__ void bulk_load(uint32_t dst, const void* src, uint32_t bytes, uint32_t bar) {
    asm volatile("cp.async.bulk.shared::cluster.global.mbarrier::complete_tx::bytes [%0], [%1], %2, [%3];" ::"r"(dst), "l"(src), "r"(bytes), "r"(bar) : "memory");
}
__device__ __forceinline__ void stsm_x4_t(uint32_t a, uint32_t r0, uint32_t r1, uint32_t r2, uint32_t r3) {
    asm volatile("stmatrix.sync.aligned.m8n8.x4.trans.shared.b16 [%0], {%1,%2,%3,%4};" ::"r"(a), "r"(r0), "r"(r1), "r"(r2), "r"(r3) : "memory");
}
#define WG_FENCE() asm volatile("wgmma.fence.sync.aligned;" ::: "memory")
#define WG_COMMIT() asm volatile("wgmma.commit_group.sync.aligned;" ::: "memory")
#define WG_WAIT(n) asm volatile("wgmma.wait_group.sync.aligned " #n ";" ::: "memory")
#define DESC_ADV(d, n) asm volatile("add.s64 %0, %0, " #n ";" : "+l"(d))
template <int N> __device__ __forceinline__ void keep(float (&a)[N]) {
#pragma unroll
    for (int i = 0; i < N; i++) asm volatile("" : "+f"(a[i])::"memory");
}
__device__ __forceinline__ uint64_t make_desc(uint32_t addr, uint32_t lbo, uint32_t sbo, uint32_t swz) {
    return (uint64_t)((addr & 0x3FFFF) >> 4) | ((uint64_t)(lbo >> 4) << 16) | ((uint64_t)(sbo >> 4) << 32) | ((uint64_t)swz << 62);
}
__device__ __forceinline__ float ex2(float x) { float y; asm("ex2.approx.ftz.f32 %0, %1;" : "=f"(y) : "f"(x)); return y; }
__device__ __forceinline__ float rcp(float x) { float y; asm("rcp.approx.ftz.f32 %0, %1;" : "=f"(y) : "f"(x)); return y; }
__device__ __forceinline__ uint32_t pack2(float lo, float hi) { uint32_t r; asm("cvt.rn.bf16x2.f32 %0, %1, %2;" : "=r"(r) : "f"(hi), "f"(lo)); return r; }
__device__ __forceinline__ float bf_lo(uint32_t v) { return __uint_as_float(v << 16); }
__device__ __forceinline__ float bf_hi(uint32_t v) { return __uint_as_float(v & 0xFFFF0000u); }

__device__ __forceinline__ void wgmma_n192_tb(float (&d)[96], uint64_t da, uint64_t db, int acc) {
    asm volatile("{ .reg .pred p; setp.ne.b32 p, %98, 0;\n"
      "wgmma.mma_async.sync.aligned.m64n192k16.f32.bf16.bf16 {%0,%1,%2,%3,%4,%5,%6,%7,%8,%9,%10,%11,%12,%13,%14,%15,%16,%17,%18,%19,%20,%21,%22,%23,%24,%25,%26,%27,%28,%29,%30,%31,%32,%33,%34,%35,%36,%37,%38,%39,%40,%41,%42,%43,%44,%45,%46,%47,%48,%49,%50,%51,%52,%53,%54,%55,%56,%57,%58,%59,%60,%61,%62,%63,%64,%65,%66,%67,%68,%69,%70,%71,%72,%73,%74,%75,%76,%77,%78,%79,%80,%81,%82,%83,%84,%85,%86,%87,%88,%89,%90,%91,%92,%93,%94,%95}, %96, %97, p, 1, 1, 0, 1; }"
      : "+f"(d[0]),"+f"(d[1]),"+f"(d[2]),"+f"(d[3]),"+f"(d[4]),"+f"(d[5]),"+f"(d[6]),"+f"(d[7]),"+f"(d[8]),"+f"(d[9]),"+f"(d[10]),"+f"(d[11]),"+f"(d[12]),"+f"(d[13]),"+f"(d[14]),"+f"(d[15]),"+f"(d[16]),"+f"(d[17]),"+f"(d[18]),"+f"(d[19]),"+f"(d[20]),"+f"(d[21]),"+f"(d[22]),"+f"(d[23]),"+f"(d[24]),"+f"(d[25]),"+f"(d[26]),"+f"(d[27]),"+f"(d[28]),"+f"(d[29]),"+f"(d[30]),"+f"(d[31]),"+f"(d[32]),"+f"(d[33]),"+f"(d[34]),"+f"(d[35]),"+f"(d[36]),"+f"(d[37]),"+f"(d[38]),"+f"(d[39]),"+f"(d[40]),"+f"(d[41]),"+f"(d[42]),"+f"(d[43]),"+f"(d[44]),"+f"(d[45]),"+f"(d[46]),"+f"(d[47]),"+f"(d[48]),"+f"(d[49]),"+f"(d[50]),"+f"(d[51]),"+f"(d[52]),"+f"(d[53]),"+f"(d[54]),"+f"(d[55]),"+f"(d[56]),"+f"(d[57]),"+f"(d[58]),"+f"(d[59]),"+f"(d[60]),"+f"(d[61]),"+f"(d[62]),"+f"(d[63]),"+f"(d[64]),"+f"(d[65]),"+f"(d[66]),"+f"(d[67]),"+f"(d[68]),"+f"(d[69]),"+f"(d[70]),"+f"(d[71]),"+f"(d[72]),"+f"(d[73]),"+f"(d[74]),"+f"(d[75]),"+f"(d[76]),"+f"(d[77]),"+f"(d[78]),"+f"(d[79]),"+f"(d[80]),"+f"(d[81]),"+f"(d[82]),"+f"(d[83]),"+f"(d[84]),"+f"(d[85]),"+f"(d[86]),"+f"(d[87]),"+f"(d[88]),"+f"(d[89]),"+f"(d[90]),"+f"(d[91]),"+f"(d[92]),"+f"(d[93]),"+f"(d[94]),"+f"(d[95])
      : "l"(da), "l"(db), "r"(acc));
}
__device__ __forceinline__ void wgmma_n128_ta(float (&d)[64], uint64_t da, uint64_t db, int acc) {
    asm volatile("{ .reg .pred p; setp.ne.b32 p, %66, 0;\n"
      "wgmma.mma_async.sync.aligned.m64n128k16.f32.bf16.bf16 {%0,%1,%2,%3,%4,%5,%6,%7,%8,%9,%10,%11,%12,%13,%14,%15,%16,%17,%18,%19,%20,%21,%22,%23,%24,%25,%26,%27,%28,%29,%30,%31,%32,%33,%34,%35,%36,%37,%38,%39,%40,%41,%42,%43,%44,%45,%46,%47,%48,%49,%50,%51,%52,%53,%54,%55,%56,%57,%58,%59,%60,%61,%62,%63}, %64, %65, p, 1, 1, 1, 0; }"
      : "+f"(d[0]),"+f"(d[1]),"+f"(d[2]),"+f"(d[3]),"+f"(d[4]),"+f"(d[5]),"+f"(d[6]),"+f"(d[7]),"+f"(d[8]),"+f"(d[9]),"+f"(d[10]),"+f"(d[11]),"+f"(d[12]),"+f"(d[13]),"+f"(d[14]),"+f"(d[15]),"+f"(d[16]),"+f"(d[17]),"+f"(d[18]),"+f"(d[19]),"+f"(d[20]),"+f"(d[21]),"+f"(d[22]),"+f"(d[23]),"+f"(d[24]),"+f"(d[25]),"+f"(d[26]),"+f"(d[27]),"+f"(d[28]),"+f"(d[29]),"+f"(d[30]),"+f"(d[31]),"+f"(d[32]),"+f"(d[33]),"+f"(d[34]),"+f"(d[35]),"+f"(d[36]),"+f"(d[37]),"+f"(d[38]),"+f"(d[39]),"+f"(d[40]),"+f"(d[41]),"+f"(d[42]),"+f"(d[43]),"+f"(d[44]),"+f"(d[45]),"+f"(d[46]),"+f"(d[47]),"+f"(d[48]),"+f"(d[49]),"+f"(d[50]),"+f"(d[51]),"+f"(d[52]),"+f"(d[53]),"+f"(d[54]),"+f"(d[55]),"+f"(d[56]),"+f"(d[57]),"+f"(d[58]),"+f"(d[59]),"+f"(d[60]),"+f"(d[61]),"+f"(d[62]),"+f"(d[63])
      : "l"(da), "l"(db), "r"(acc));
}
__device__ __forceinline__ void wgmma_n64_tb(float (&d)[32], uint64_t da, uint64_t db, int acc) {
    asm volatile("{ .reg .pred p; setp.ne.b32 p, %34, 0;\n"
      "wgmma.mma_async.sync.aligned.m64n64k16.f32.bf16.bf16 {%0,%1,%2,%3,%4,%5,%6,%7,%8,%9,%10,%11,%12,%13,%14,%15,%16,%17,%18,%19,%20,%21,%22,%23,%24,%25,%26,%27,%28,%29,%30,%31}, %32, %33, p, 1, 1, 0, 1; }"
      : "+f"(d[0]),"+f"(d[1]),"+f"(d[2]),"+f"(d[3]),"+f"(d[4]),"+f"(d[5]),"+f"(d[6]),"+f"(d[7]),"+f"(d[8]),"+f"(d[9]),"+f"(d[10]),"+f"(d[11]),"+f"(d[12]),"+f"(d[13]),"+f"(d[14]),"+f"(d[15]),"+f"(d[16]),"+f"(d[17]),"+f"(d[18]),"+f"(d[19]),"+f"(d[20]),"+f"(d[21]),"+f"(d[22]),"+f"(d[23]),"+f"(d[24]),"+f"(d[25]),"+f"(d[26]),"+f"(d[27]),"+f"(d[28]),"+f"(d[29]),"+f"(d[30]),"+f"(d[31])
      : "l"(da), "l"(db), "r"(acc));
}
__device__ __forceinline__ void wgmma_qk(float (&d)[32], const uint32_t* a, uint64_t db) {
    asm volatile("wgmma.mma_async.sync.aligned.m64n64k16.f32.bf16.bf16 {%0,%1,%2,%3,%4,%5,%6,%7,%8,%9,%10,%11,%12,%13,%14,%15,%16,%17,%18,%19,%20,%21,%22,%23,%24,%25,%26,%27,%28,%29,%30,%31}, {%32,%33,%34,%35}, %36, 0, 1, 1, 0;"
      : "=f"(d[0]),"=f"(d[1]),"=f"(d[2]),"=f"(d[3]),"=f"(d[4]),"=f"(d[5]),"=f"(d[6]),"=f"(d[7]),"=f"(d[8]),"=f"(d[9]),"=f"(d[10]),"=f"(d[11]),"=f"(d[12]),"=f"(d[13]),"=f"(d[14]),"=f"(d[15]),"=f"(d[16]),"=f"(d[17]),"=f"(d[18]),"=f"(d[19]),"=f"(d[20]),"=f"(d[21]),"=f"(d[22]),"=f"(d[23]),"=f"(d[24]),"=f"(d[25]),"=f"(d[26]),"=f"(d[27]),"=f"(d[28]),"=f"(d[29]),"=f"(d[30]),"=f"(d[31])
      : "r"(a[0]), "r"(a[1]), "r"(a[2]), "r"(a[3]), "l"(db));
}
__device__ __forceinline__ void wgmma_pv(float (&d)[12], const uint32_t* a, uint64_t db) {
    asm volatile("wgmma.mma_async.sync.aligned.m64n24k16.f32.bf16.bf16 {%0,%1,%2,%3,%4,%5,%6,%7,%8,%9,%10,%11}, {%12,%13,%14,%15}, %16, 1, 1, 1, 1;"
      : "+f"(d[0]),"+f"(d[1]),"+f"(d[2]),"+f"(d[3]),"+f"(d[4]),"+f"(d[5]),"+f"(d[6]),"+f"(d[7]),"+f"(d[8]),"+f"(d[9]),"+f"(d[10]),"+f"(d[11])
      : "r"(a[0]), "r"(a[1]), "r"(a[2]), "r"(a[3]), "l"(db));
}

constexpr int K1_A = 0, K1_B = 131072, K1_STAGE = 24576, K1_NST = 4, K1_BAR = K1_B + K1_NST * K1_STAGE, K1_SMEM = K1_BAR + 128;
constexpr float Q_SCALE = 0.25f * 1.4426950408889634f;

__global__ void __launch_bounds__(288, 1)
k1_ln_qkv(const __grid_constant__ CUtensorMap tm_x, const __grid_constant__ CUtensorMap tm_wqkv) {
    extern __shared__ __align__(1024) uint8_t smem[];
    const uint32_t sb = smem_u32(smem);
    const uint32_t bar_x = sb + K1_BAR, bar_full = bar_x + 8, bar_empty = bar_full + 8 * K1_NST;
    const int tid = threadIdx.x, lane = tid & 31, warp = tid >> 5;
    const int rt = blockIdx.x >> 3, ct = blockIdx.x & 7;
    if (tid == 0) {
        mbar_init(bar_x, 1);
        for (int i = 0; i < K1_NST; i++) { mbar_init(bar_full + 8 * i, 1); mbar_init(bar_empty + 8 * i, 8); }
        fence_bar_init();
    }
    if (blockIdx.x == 0 && tid < 16) g_flag[tid] = 0;
    __syncthreads();
    pdl_launch();
    if (warp == 8) {
        if (lane == 0) {
            mbar_expect(bar_x, 131072);
            for (int kb = 0; kb < 8; kb++) tma_load(sb + K1_A + kb * 16384, &tm_x, kb * 64, rt * 128, bar_x);
            for (int kb = 0; kb < 8; kb++) {
                const int st = kb & 3;
                if (kb >= K1_NST) mbar_wait(bar_empty + 8 * st, 0);
                mbar_expect(bar_full + 8 * st, K1_STAGE);
                for (int b = 0; b < 3; b++) tma_load(sb + K1_B + st * K1_STAGE + b * 8192, &tm_wqkv, ct * 192 + b * 64, kb * 64, bar_full + 8 * st);
            }
        }
        return;
    }
    mbar_wait(bar_x, 0);
    {
        const int kb0 = lane >> 3, ch = lane & 7;
#pragma unroll 1
        for (int r0 = 0; r0 < 16; r0 += 4) {
            float v[4][16];
#pragma unroll
            for (int i = 0; i < 4; i++) {
                const int r = warp * 16 + r0 + i;
                const uint8_t* p = smem + K1_A + kb0 * 16384 + r * 128 + ((ch ^ (r & 7)) << 4);
                const uint4 a = *(const uint4*)p, b = *(const uint4*)(p + 4 * 16384);
                const uint32_t w[8] = {a.x, a.y, a.z, a.w, b.x, b.y, b.z, b.w};
#pragma unroll
                for (int j = 0; j < 8; j++) { v[i][2 * j] = bf_lo(w[j]); v[i][2 * j + 1] = bf_hi(w[j]); }
            }
            float mean[4], rstd[4];
#pragma unroll
            for (int i = 0; i < 4; i++) {
                float s = 0.f;
#pragma unroll
                for (int j = 0; j < 16; j++) s += v[i][j];
                mean[i] = s;
            }
#pragma unroll
            for (int o = 16; o > 0; o >>= 1)
#pragma unroll
                for (int i = 0; i < 4; i++) mean[i] += __shfl_xor_sync(~0u, mean[i], o);
#pragma unroll
            for (int i = 0; i < 4; i++) {
                mean[i] *= (1.f / D);
                float s = 0.f;
#pragma unroll
                for (int j = 0; j < 16; j++) { v[i][j] -= mean[i]; s = fmaf(v[i][j], v[i][j], s); }
                rstd[i] = s;
            }
#pragma unroll
            for (int o = 16; o > 0; o >>= 1)
#pragma unroll
                for (int i = 0; i < 4; i++) rstd[i] += __shfl_xor_sync(~0u, rstd[i], o);
#pragma unroll
            for (int i = 0; i < 4; i++) {
                const float rs = rsqrtf(rstd[i] * (1.f / D) + 1e-5f);
                const int r = warp * 16 + r0 + i;
                uint4 a, b;
                a.x = pack2(v[i][0] * rs, v[i][1] * rs);   a.y = pack2(v[i][2] * rs, v[i][3] * rs);
                a.z = pack2(v[i][4] * rs, v[i][5] * rs);   a.w = pack2(v[i][6] * rs, v[i][7] * rs);
                b.x = pack2(v[i][8] * rs, v[i][9] * rs);   b.y = pack2(v[i][10] * rs, v[i][11] * rs);
                b.z = pack2(v[i][12] * rs, v[i][13] * rs); b.w = pack2(v[i][14] * rs, v[i][15] * rs);
                uint8_t* p = smem + K1_A + kb0 * 16384 + r * 128 + ((ch ^ (r & 7)) << 4);
                *(uint4*)p = a;
                *(uint4*)(p + 4 * 16384) = b;
                if (warp == ct) {
                    uint4* g = (uint4*)(g_xn + (size_t)(rt * 128 + r) * D);
                    g[lane] = a;
                    g[32 + lane] = b;
                }
            }
        }
    }
    fence_async_smem();
    named_bar(1, 256);
    const int wg = warp >> 2;
    float acc[96];
    {
        const uint64_t da0 = make_desc(sb + K1_A + wg * 8192, 16, 1024, 1);
        const uint64_t db0 = make_desc(sb + K1_B, 8192, 1024, 1);
#pragma unroll 1
        for (int kb = 0; kb < 8; kb++) {
            const int st = kb & 3;
            mbar_wait(bar_full + 8 * st, kb >> 2);
            const uint64_t da = da0 + kb * (16384 >> 4), db = db0 + st * (K1_STAGE >> 4);
            WG_FENCE();
#pragma unroll
            for (int k = 0; k < 4; k++) wgmma_n192_tb(acc, da + k * 2, db + k * 128, kb | k);
            WG_COMMIT();
            if (kb >= 1 && kb < 5) {
                WG_WAIT(1);
                if (lane == 0) mbar_arrive(bar_empty + 8 * ((kb - 1) & 3));
            }
        }
        WG_WAIT(0);
        keep(acc);
    }
    {
        const int g = lane >> 2, t = lane & 3;
        const int tok = rt * 128 + wg * 64 + (warp & 3) * 16 + g;
        uint32_t* base = (uint32_t*)g_qkv;
#pragma unroll
        for (int j = 0; j < 24; j++) {
            const int col = ct * 192 + j * 8;
            const int plane = col >> 3;
            const float sc = (col < D) ? Q_SCALE : 1.f;
            uint32_t* p = base + ((size_t)plane * S + tok) * 4 + t;
            p[0] = pack2(acc[4 * j] * sc, acc[4 * j + 1] * sc);
            p[32] = pack2(acc[4 * j + 2] * sc, acc[4 * j + 3] * sc);
        }
    }
}

constexpr int K2_X = 0, K2_W = 131072, K2_RING = K2_W + 3 * 8192, K2_RSTAGE = 20480, K2_STG = K2_RING + 3 * K2_RSTAGE;
constexpr int K2_BAR = K2_STG + 8192, K2_SMEM = K2_BAR + 256;
constexpr int K2_DSTAGE = 24576, K2_DNST = 5;
constexpr int K2_THREADS = 640;
#define POLY_MASK 0xDADA
constexpr float REF_OFFSET = 80.f;
constexpr float POLY_LOG2K = -0.052214f;

struct PolyC { uint32_t one, e2; };
__device__ __forceinline__ uint32_t exp2_soft(float a, float b, float bz, const PolyC& c) {
    float ra, rb;
    asm("fma.rn.sat.f32 %0, %1, 0f00000080, %2;" : "=f"(ra) : "f"(a), "f"(bz));
    asm("fma.rn.sat.f32 %0, %1, 0f00000080, %2;" : "=f"(rb) : "f"(b), "f"(bz));
    uint32_t W, G, d, Y;
    asm("cvt.pack.sat.s16.s32 %0, %1, %2;" : "=r"(W) : "r"(__float_as_uint(rb)), "r"(__float_as_uint(ra)));
    asm("lop3.b32 %0, %1, 0x007F007F, %2, 0xEA;" : "=r"(G) : "r"(W), "r"(c.one));
    asm("fma.rn.bf16x2 %0, %1, %2, %3;" : "=r"(d) : "r"(G), "r"(c.e2), "r"(0xBF27BF27u));
    asm("fma.rn.bf16x2 %0, %1, %2, %3;" : "=r"(d) : "r"(G), "r"(d), "r"(0x3EC83EC8u));
    asm("fma.rn.bf16x2 %0, %1, %2, %1;" : "=r"(Y) : "r"(W), "r"(d));
    return Y;
}
__device__ __forceinline__ void softmax_step(const float (&s)[32], uint32_t (&p)[16], float nm0, float nm1, float bz0, float bz1, const PolyC& c) {
#pragma unroll
    for (int i = 0; i < 16; i++)
        if (!((POLY_MASK >> i) & 1)) { const float nm = (i & 1) ? nm1 : nm0; p[i] = pack2(ex2(s[2 * i] + nm), ex2(s[2 * i + 1] + nm)); }
#pragma unroll
    for (int i = 0; i < 16; i++)
        if ((POLY_MASK >> i) & 1) p[i] = exp2_soft(s[2 * i], s[2 * i + 1], (i & 1) ? bz1 : bz0, c);
}
__device__ __forceinline__ void mma16816(float (&d)[4], const uint32_t* a, uint32_t b0, uint32_t b1) {
    asm volatile("mma.sync.aligned.m16n8k16.row.col.f32.bf16.bf16.f32 {%0,%1,%2,%3},{%4,%5,%6,%7},{%8,%9},{%0,%1,%2,%3};"
                 : "+f"(d[0]), "+f"(d[1]), "+f"(d[2]), "+f"(d[3]) : "r"(a[0]), "r"(a[1]), "r"(a[2]), "r"(a[3]), "r"(b0), "r"(b1));
}
__device__ __forceinline__ void attn_rows_true_max(const uint32_t (&qf)[4], const uint4* gk, const uint4* gv, __nv_bfloat16* orow, int lane) {
    const int g = lane >> 2, t = lane & 3;
    const uint32_t* k0 = (const uint32_t*)gk;
    const uint32_t* k1 = (const uint32_t*)(gk + S);
    float m0 = -INFINITY, m1 = -INFINITY;
#pragma unroll 1
    for (int kb = 0; kb < S / 8; kb++) {
        float s[4] = {0.f, 0.f, 0.f, 0.f};
        mma16816(s, qf, k0[(kb * 8 + g) * 4 + t], k1[(kb * 8 + g) * 4 + t]);
        m0 = fmaxf(m0, fmaxf(s[0], s[1]));
        m1 = fmaxf(m1, fmaxf(s[2], s[3]));
    }
    m0 = fmaxf(m0, __shfl_xor_sync(~0u, m0, 1)); m0 = fmaxf(m0, __shfl_xor_sync(~0u, m0, 2));
    m1 = fmaxf(m1, __shfl_xor_sync(~0u, m1, 1)); m1 = fmaxf(m1, __shfl_xor_sync(~0u, m1, 2));
    float o0[4] = {0.f, 0.f, 0.f, 0.f}, o1[4] = {0.f, 0.f, 0.f, 0.f}, l0 = 0.f, l1 = 0.f;
    const uint16_t* v0 = (const uint16_t*)gv;
    const uint16_t* v1 = (const uint16_t*)(gv + S);
#pragma unroll 1
    for (int kb = 0; kb < S / 16; kb++) {
        float sa[4] = {0.f, 0.f, 0.f, 0.f}, sc[4] = {0.f, 0.f, 0.f, 0.f};
        mma16816(sa, qf, k0[(kb * 16 + g) * 4 + t], k1[(kb * 16 + g) * 4 + t]);
        mma16816(sc, qf, k0[(kb * 16 + 8 + g) * 4 + t], k1[(kb * 16 + 8 + g) * 4 + t]);
        uint32_t p[4];
        p[0] = pack2(ex2(sa[0] - m0), ex2(sa[1] - m0));
        p[1] = pack2(ex2(sa[2] - m1), ex2(sa[3] - m1));
        p[2] = pack2(ex2(sc[0] - m0), ex2(sc[1] - m0));
        p[3] = pack2(ex2(sc[2] - m1), ex2(sc[3] - m1));
        l0 += bf_lo(p[0]) + bf_hi(p[0]) + bf_lo(p[2]) + bf_hi(p[2]);
        l1 += bf_lo(p[1]) + bf_hi(p[1]) + bf_lo(p[3]) + bf_hi(p[3]);
        const int key = kb * 16 + 2 * t;
        mma16816(o0, p, v0[key * 8 + g] | ((uint32_t)v0[(key + 1) * 8 + g] << 16), v0[(key + 8) * 8 + g] | ((uint32_t)v0[(key + 9) * 8 + g] << 16));
        mma16816(o1, p, v1[key * 8 + g] | ((uint32_t)v1[(key + 1) * 8 + g] << 16), v1[(key + 8) * 8 + g] | ((uint32_t)v1[(key + 9) * 8 + g] << 16));
    }
    l0 += __shfl_xor_sync(~0u, l0, 1); l0 += __shfl_xor_sync(~0u, l0, 2);
    l1 += __shfl_xor_sync(~0u, l1, 1); l1 += __shfl_xor_sync(~0u, l1, 2);
    const float i0 = 1.f / l0, i1 = 1.f / l1;
    *(uint32_t*)(orow + 2 * t) = pack2(o0[0] * i0, o0[1] * i0);
    *(uint32_t*)(orow + 8 + 2 * t) = pack2(o1[0] * i0, o1[1] * i0);
    *(uint32_t*)(orow + 8 * D + 2 * t) = pack2(o0[2] * i1, o0[3] * i1);
    *(uint32_t*)(orow + 8 * D + 8 + 2 * t) = pack2(o1[2] * i1, o1[3] * i1);
}

__global__ void __launch_bounds__(K2_THREADS, 1)
k2_attn_ffn(const __grid_constant__ CUtensorMap tm_xn, const __grid_constant__ CUtensorMap tm_wg, const __grid_constant__ CUtensorMap tm_wu,
            const __grid_constant__ CUtensorMap tm_wd, const __grid_constant__ CUtensorMap tm_h_ld, const __grid_constant__ CUtensorMap tm_h_st,
            const __grid_constant__ CUtensorMap tm_g, uint32_t zero) {
    extern __shared__ __align__(1024) uint8_t smem[];
    const uint32_t sb = smem_u32(smem);
    const uint32_t bar_rfull = sb + K2_BAR, cnt_ring = bar_rfull + 24;
    const uint32_t bar_x = cnt_ring + 24, bar_w = bar_x + 64, bar_d = bar_w + 24;
    const int tid = threadIdx.x, lane = tid & 31;
    const int wg = __shfl_sync(~0u, tid >> 7, 0);
    if (tid == 0) {
        for (int i = 0; i < 3; i++) { mbar_init(bar_rfull + 8 * i, 1); *(uint32_t*)(smem + K2_BAR + 24 + 8 * i) = 0; mbar_init(bar_w + 8 * i, 1); }
        for (int i = 0; i < 8; i++) mbar_init(bar_x + 8 * i, 1);
        for (int i = 0; i < K2_DNST; i++) mbar_init(bar_d + 8 * i, 1);
        fence_bar_init();
    }
    for (int i = tid; i < 3 * 256; i += K2_THREADS) *(uint4*)(smem + K2_RING + (i >> 8) * K2_RSTAGE + 16384 + (i & 255) * 16) = make_uint4(0x00003F80u, 0, 0, 0);
    fence_async_smem();
    __syncthreads();
    pdl_launch();
    pdl_wait();

    if (wg < 4) {
        const int head = blockIdx.x >> 2, part = blockIdx.x & 3;
        const int warp4 = (tid >> 5) & 3;
        const uint4* gq = g_qkv + (size_t)(0 * H + head) * 2 * S;
        const uint4* gk = g_qkv + (size_t)(1 * H + head) * 2 * S;
        const uint4* gv = g_qkv + (size_t)(2 * H + head) * 2 * S;
        PolyC pc;
        pc.one = 0x3F803F80u ^ zero;
        pc.e2 = 0x3E623E62u ^ zero;
        const uint64_t dk0 = make_desc(sb + K2_RING, 4096, 128, 0), dv0 = make_desc(sb + K2_RING + 8192, 128, 4096, 0);
        auto ring_fill = [&](int n, int stage) {
            const int c = n & 7;
            const uint32_t b = bar_rfull + 8 * stage, dst = sb + K2_RING + stage * K2_RSTAGE;
            mbar_expect(b, 16384);
            bulk_load(dst, gk + c * 256, 4096, b);
            bulk_load(dst + 4096, gk + S + c * 256, 4096, b);
            bulk_load(dst + 8192, gv + c * 256, 4096, b);
            bulk_load(dst + 12288, gv + S + c * 256, 4096, b);
        };
        auto ring_release = [&](int stage) {
            uint32_t old;
            asm volatile("atom.acq_rel.cta.shared::cta.add.u32 %0, [%1], 1;" : "=r"(old) : "r"(cnt_ring + 8 * stage) : "memory");
            return old;
        };
        if (tid == 0) { ring_fill(0, 0); ring_fill(1, 1); ring_fill(2, 2); }
        int st = 0, ph = 0;
#pragma unroll 1
        for (int rnd = 0; rnd < 2; rnd++) {
            const int row0 = part * 512 + (rnd * 4 + wg) * 64 + warp4 * 16;
            uint32_t qf[4];
            {
                const uint32_t* qp = (const uint32_t*)(gq + row0 + (lane >> 2)) + (lane & 3);
                qf[0] = qp[0]; qf[1] = qp[32]; qf[2] = qp[S * 4]; qf[3] = qp[S * 4 + 32];
            }
            float s[32], o[12];
            uint32_t p[16];
            mbar_wait(bar_rfull + 8 * st, ph);
            uint64_t dk = dk0 + st * (K2_RSTAGE >> 4), dv;
            WG_FENCE(); wgmma_qk(s, qf, dk); WG_COMMIT(); WG_WAIT(0); keep(s);
            float m0 = -INFINITY, m1 = -INFINITY;
#pragma unroll
            for (int i = 0; i < 32; i += 4) { m0 = fmaxf(m0, fmaxf(s[i], s[i + 1])); m1 = fmaxf(m1, fmaxf(s[i + 2], s[i + 3])); }
            m0 = fmaxf(m0, __shfl_xor_sync(~0u, m0, 1)); m0 = fmaxf(m0, __shfl_xor_sync(~0u, m0, 2));
            m1 = fmaxf(m1, __shfl_xor_sync(~0u, m1, 1)); m1 = fmaxf(m1, __shfl_xor_sync(~0u, m1, 2));
            m0 = ceilf(m0) + REF_OFFSET; m1 = ceilf(m1) + REF_OFFSET;
            float nm0 = POLY_LOG2K - m0, nm1 = POLY_LOG2K - m1;
            float bz0 = __fmul_rn(__fmul_rn(127.0f - m0, 0x1p-71f), 0x1p-71f), bz1 = __fmul_rn(__fmul_rn(127.0f - m1, 0x1p-71f), 0x1p-71f);
            asm volatile("" : "+f"(nm0), "+f"(nm1), "+f"(bz0), "+f"(bz1));
#pragma unroll
            for (int i = 0; i < 12; i++) o[i] = 0.f;
            int prev = -1;
#pragma unroll 1
            for (int c = 0; c < 8; c++) {
                if (c > 0) mbar_wait(bar_rfull + 8 * st, ph);
                dk = dk0 + st * (K2_RSTAGE >> 4);
                dv = dv0 + st * (K2_RSTAGE >> 4);
#pragma unroll
                for (int u = 0; u < 4; u++) {
                    WG_FENCE(); wgmma_qk(s, qf, dk); DESC_ADV(dk, 64); WG_COMMIT(); WG_WAIT(0); keep(s);
                    uint32_t old = 0;
                    if (u == 0 && prev >= 0 && lane == 0) old = ring_release(prev);
                    softmax_step(s, p, nm0, nm1, bz0, bz1, pc);
                    if (u == 0 && (old & 15) == 15 && rnd * 8 + c + 2 < 16) ring_fill(rnd * 8 + c + 2, prev);
                    WG_FENCE();
                    wgmma_pv(o, p, dv); DESC_ADV(dv, 16);
                    wgmma_pv(o, p + 4, dv); DESC_ADV(dv, 16);
                    wgmma_pv(o, p + 8, dv); DESC_ADV(dv, 16);
                    wgmma_pv(o, p + 12, dv); DESC_ADV(dv, 16);
                    WG_COMMIT();
                }
                prev = st;
                if (++st == 3) { st = 0; ph ^= 1; }
            }
            WG_WAIT(0);
            keep(o);
            if (lane == 0) {
                const uint32_t old = ring_release(prev);
                if ((old & 15) == 15 && rnd == 0) ring_fill(10, prev);
            }
            const float l0 = __shfl_sync(~0u, o[8], lane & ~3), l1 = __shfl_sync(~0u, o[10], lane & ~3);
            bool bad = !(l0 < 0x1p120f) || !(l1 < 0x1p120f);
#pragma unroll
            for (int i = 0; i < 8; i++) bad = bad || !(fabsf(o[i]) < INFINITY);
            __nv_bfloat16* orow = g_o + (size_t)(row0 + (lane >> 2)) * D + head * 16;
            if (__any_sync(~0u, bad)) {
                attn_rows_true_max(qf, gk, gv, orow, lane);
            } else {
                const float i0 = rcp(l0), i1 = rcp(l1);
                const int t = lane & 3;
                *(uint32_t*)(orow + 2 * t) = pack2(o[0] * i0, o[1] * i0);
                *(uint32_t*)(orow + 8 + 2 * t) = pack2(o[4] * i0, o[5] * i0);
                *(uint32_t*)(orow + 8 * D + 2 * t) = pack2(o[2] * i1, o[3] * i1);
                *(uint32_t*)(orow + 8 * D + 8 + 2 * t) = pack2(o[6] * i1, o[7] * i1);
            }
        }
    } else {
        const int rt = blockIdx.x >> 3, ct = blockIdx.x & 7;
        const int w = (tid >> 5) & 3;
        const bool leader = (tid == 512);
        float acc[64];
        if (leader) {
            for (int kb = 0; kb < 8; kb++) { mbar_expect(bar_x + 8 * kb, 16384); tma_load(sb + K2_X + kb * 16384, &tm_xn, kb * 64, rt * 128, bar_x + 8 * kb); }
            for (int n = 0; n < 3; n++) {
                mbar_expect(bar_w + 8 * n, 8192);
                tma_load(sb + K2_W + n * 8192, &tm_wg, ct * 224, n * 64, bar_w + 8 * n);
                tma_load(sb + K2_W + n * 8192 + 4096, &tm_wu, ct * 224, n * 64, bar_w + 8 * n);
            }
        }
        {
            const uint64_t da0 = make_desc(sb + K2_W, 4096, 512, 2), db0 = make_desc(sb + K2_X, 16, 1024, 1);
            int wst = 0, wph = 0;
#pragma unroll 1
            for (int tile = 0; tile < 7; tile++) {
#pragma unroll 1
                for (int kb = 0; kb < 8; kb++) {
                    if (tile == 0) mbar_wait(bar_x + 8 * kb, 0);
                    mbar_wait(bar_w + 8 * wst, wph);
                    const uint64_t da = da0 + wst * (8192 >> 4), db = db0 + kb * (16384 >> 4);
                    WG_FENCE();
#pragma unroll
                    for (int k = 0; k < 4; k++) wgmma_n128_ta(acc, da + k * 64, db + k * 2, kb | k);
                    WG_COMMIT();
                    WG_WAIT(0);
                    named_bar(2, 128);
                    const int n = tile * 8 + kb + 3;
                    if (leader && n < 56) {
                        mbar_expect(bar_w + 8 * wst, 8192);
                        tma_load(sb + K2_W + wst * 8192, &tm_wg, ct * 224 + (n >> 3) * 32, (n & 7) * 64, bar_w + 8 * wst);
                        tma_load(sb + K2_W + wst * 8192 + 4096, &tm_wu, ct * 224 + (n >> 3) * 32, (n & 7) * 64, bar_w + 8 * wst);
                    }
                    if (++wst == 3) { wst = 0; wph ^= 1; }
                }
                keep(acc);
                const int type = w >> 1, fw = w & 1;
                uint32_t pk[32];
#pragma unroll
                for (int i = 0; i < 32; i++) pk[i] = pack2(acc[2 * i], acc[2 * i + 1]);
                if (leader) asm volatile("cp.async.bulk.wait_group.read 0;" ::: "memory");
                named_bar(2, 128);
                uint4* xs = (uint4*)(smem + K2_STG) + w * 128 + lane;
#pragma unroll
                for (int i = 0; i < 4; i++) {
                    xs[i * 32] = type ? make_uint4(pk[4 * i], pk[4 * i + 1], pk[4 * i + 2], pk[4 * i + 3])
                                      : make_uint4(pk[16 + 4 * i], pk[16 + 4 * i + 1], pk[16 + 4 * i + 2], pk[16 + 4 * i + 3]);
                }
                named_bar(2, 128);
                const uint4* xr = (const uint4*)(smem + K2_STG) + (w ^ 2) * 128 + lane;
                uint32_t hv[16];
#pragma unroll
                for (int i = 0; i < 4; i++) {
                    const uint4 r = xr[i * 32];
                    const uint32_t rr[4] = {r.x, r.y, r.z, r.w};
#pragma unroll
                    for (int e = 0; e < 4; e++) {
                        const uint32_t mine = type ? pk[16 + 4 * i + e] : pk[4 * i + e];
                        asm("mul.rn.bf16x2 %0, %1, %2;" : "=r"(hv[4 * i + e]) : "r"(mine), "r"(rr[e]));
                    }
                }
                named_bar(2, 128);
#pragma unroll
                for (int i = 0; i < 4; i++) {
                    const int mi = lane >> 3;
                    const int tok = 8 * (2 * i + (mi >> 1) + 8 * type) + (lane & 7);
                    const int chunk = 2 * fw + (mi & 1);
                    stsm_x4_t(sb + K2_STG + tok * 64 + ((chunk ^ ((tok >> 1) & 3)) << 4), hv[4 * i], hv[4 * i + 1], hv[4 * i + 2], hv[4 * i + 3]);
                }
                fence_async_smem();
                named_bar(2, 128);
                if (leader) tma_store(&tm_h_st, ct * 224 + tile * 32, rt * 128, sb + K2_STG);
            }
        }
        if (leader) {
            asm volatile("cp.async.bulk.wait_group 0;" ::: "memory");
            __threadfence();
            atomicAdd(&g_flag[rt], 1u);
            unsigned v;
            int spin = 0;
            do {
                asm volatile("ld.acquire.gpu.global.u32 %0, [%1];" : "=r"(v) : "l"(&g_flag[rt]) : "memory");
                if (v < 8) __nanosleep(200);
            } while (v < 8 && ++spin < (1 << 22));
            if (v < 8) __trap();
            asm volatile("fence.proxy.async;" ::: "memory");
            for (int n = 0; n < K2_DNST; n++) {
                mbar_expect(bar_d + 8 * n, K2_DSTAGE);
                tma_load(sb + K2_X + n * K2_DSTAGE, &tm_wd, ct * 64, n * 64, bar_d + 8 * n);
                tma_load(sb + K2_X + n * K2_DSTAGE + 8192, &tm_h_ld, n * 64, rt * 128, bar_d + 8 * n);
            }
        }
        {
            const uint64_t da0 = make_desc(sb + K2_X, 16, 1024, 1), db0 = make_desc(sb + K2_X + 8192, 16, 1024, 1);
            int st = 0, ph = 0;
#pragma unroll 1
            for (int kb = 0; kb < 28; kb++) {
                mbar_wait(bar_d + 8 * st, ph);
                const uint64_t da = da0 + st * (K2_DSTAGE >> 4), db = db0 + st * (K2_DSTAGE >> 4);
                WG_FENCE();
#pragma unroll
                for (int k = 0; k < 4; k++) wgmma_n128_ta(acc, da + k * 128, db + k * 2, kb | k);
                WG_COMMIT();
                WG_WAIT(0);
                named_bar(2, 128);
                const int n = kb + K2_DNST;
                if (leader && n < 28) {
                    mbar_expect(bar_d + 8 * st, K2_DSTAGE);
                    tma_load(sb + K2_X + st * K2_DSTAGE, &tm_wd, ct * 64, n * 64, bar_d + 8 * st);
                    tma_load(sb + K2_X + st * K2_DSTAGE + 8192, &tm_h_ld, n * 64, rt * 128, bar_d + 8 * st);
                }
                if (++st == K2_DNST) { st = 0; ph ^= 1; }
            }
            keep(acc);
            uint32_t gv[32];
#pragma unroll
            for (int i = 0; i < 32; i++) {
                const float y0 = acc[2 * i], y1 = acc[2 * i + 1];
                gv[i] = pack2(__fdividef(y0, 1.f + __expf(-y0)), __fdividef(y1, 1.f + __expf(-y1)));
            }
#pragma unroll
            for (int i = 0; i < 8; i++) {
                const int mi = lane >> 3;
                const int tok = 8 * (2 * i + (mi >> 1)) + (lane & 7);
                const int chunk = 2 * w + (mi & 1);
                stsm_x4_t(sb + K2_W + tok * 128 + ((chunk ^ (tok & 7)) << 4), gv[4 * i], gv[4 * i + 1], gv[4 * i + 2], gv[4 * i + 3]);
            }
            fence_async_smem();
            named_bar(2, 128);
            if (leader) {
                tma_store(&tm_g, ct * 64, rt * 128, sb + K2_W);
                asm volatile("cp.async.bulk.wait_group 0;" ::: "memory");
            }
        }
    }
}

constexpr int K3_A = 0, K3_B = 131072, K3_BAR = K3_B + 65536, K3_SMEM = K3_BAR + 128;

__global__ void __launch_bounds__(256, 1)
k3_out(const __grid_constant__ CUtensorMap tm_o, const __grid_constant__ CUtensorMap tm_wo, const __nv_bfloat16* __restrict__ x, __nv_bfloat16* __restrict__ out) {
    extern __shared__ __align__(1024) uint8_t smem[];
    const uint32_t sb = smem_u32(smem);
    const uint32_t bar_a = sb + K3_BAR, bar_b = bar_a + 64;
    const int tid = threadIdx.x, lane = tid & 31, warp = tid >> 5;
    const int rt = blockIdx.x >> 3, ct = blockIdx.x & 7;
    if (tid == 0) {
        for (int i = 0; i < 8; i++) mbar_init(bar_a + 8 * i, 1);
        mbar_init(bar_b, 1);
        fence_bar_init();
        mbar_expect(bar_b, 65536);
        for (int kb = 0; kb < 8; kb++) tma_load(sb + K3_B + kb * 8192, &tm_wo, ct * 64, kb * 64, bar_b);
    }
    const int wg = warp >> 2, g = lane >> 2, t = lane & 3;
    const size_t e0 = (size_t)(rt * 128 + wg * 64 + (warp & 3) * 16 + g) * D + ct * 64 + 2 * t;
    uint32_t xv[16], gv[16];
#pragma unroll
    for (int j = 0; j < 8; j++) { xv[2 * j] = *(const uint32_t*)(x + e0 + 8 * j); xv[2 * j + 1] = *(const uint32_t*)(x + e0 + 8 * D + 8 * j); }
    __syncthreads();
    pdl_wait();
    if (tid == 0) {
        for (int kb = 0; kb < 8; kb++) { mbar_expect(bar_a + 8 * kb, 16384); tma_load(sb + K3_A + kb * 16384, &tm_o, kb * 64, rt * 128, bar_a + 8 * kb); }
    }
#pragma unroll
    for (int j = 0; j < 8; j++) { gv[2 * j] = *(const uint32_t*)(g_g + e0 + 8 * j); gv[2 * j + 1] = *(const uint32_t*)(g_g + e0 + 8 * D + 8 * j); }
    float acc[32];
    const uint64_t da0 = make_desc(sb + K3_A + wg * 8192, 16, 1024, 1), db0 = make_desc(sb + K3_B, 8192, 1024, 1);
    mbar_wait(bar_b, 0);
#pragma unroll 1
    for (int kb = 0; kb < 8; kb++) {
        mbar_wait(bar_a + 8 * kb, 0);
        WG_FENCE();
#pragma unroll
        for (int k = 0; k < 4; k++) wgmma_n64_tb(acc, da0 + kb * (16384 >> 4) + k * 2, db0 + kb * (8192 >> 4) + k * 128, kb | k);
        WG_COMMIT();
    }
    WG_WAIT(0);
    keep(acc);
#pragma unroll
    for (int j = 0; j < 8; j++) {
        *(uint32_t*)(out + e0 + 8 * j) = pack2(fmaf(acc[4 * j], bf_lo(gv[2 * j]), bf_lo(xv[2 * j])), fmaf(acc[4 * j + 1], bf_hi(gv[2 * j]), bf_hi(xv[2 * j])));
        *(uint32_t*)(out + e0 + 8 * D + 8 * j) =
            pack2(fmaf(acc[4 * j + 2], bf_lo(gv[2 * j + 1]), bf_lo(xv[2 * j + 1])), fmaf(acc[4 * j + 3], bf_hi(gv[2 * j + 1]), bf_hi(xv[2 * j + 1])));
    }
}

typedef CUresult (*EncodeFn)(CUtensorMap*, CUtensorMapDataType, cuuint32_t, void*, const cuuint64_t*, const cuuint64_t*, const cuuint32_t*,
                             const cuuint32_t*, CUtensorMapInterleave, CUtensorMapSwizzle, CUtensorMapL2promotion, CUtensorMapFloatOOBfill);

CUtensorMap make_map(EncodeFn fn, const void* ptr, int rows, int cols, int box_rows, int box_cols, CUtensorMapSwizzle swz) {
    CUtensorMap m;
    const cuuint64_t dims[2] = {(cuuint64_t)cols, (cuuint64_t)rows};
    const cuuint64_t strides[1] = {(cuuint64_t)cols * 2};
    const cuuint32_t box[2] = {(cuuint32_t)box_cols, (cuuint32_t)box_rows};
    const cuuint32_t estr[2] = {1, 1};
    fn(&m, CU_TENSOR_MAP_DATA_TYPE_BFLOAT16, 2, const_cast<void*>(ptr), dims, strides, box, estr, CU_TENSOR_MAP_INTERLEAVE_NONE, swz,
       CU_TENSOR_MAP_L2_PROMOTION_L2_256B, CU_TENSOR_MAP_FLOAT_OOB_FILL_NONE);
    return m;
}

template <typename... KArgs, typename... Args>
void launch(void (*kern)(KArgs...), int grid, int block, int smem, bool pdl, Args... args) {
    cudaLaunchConfig_t cfg = {};
    cfg.gridDim = dim3(grid);
    cfg.blockDim = dim3(block);
    cfg.dynamicSmemBytes = smem;
    cfg.stream = cudaStreamPerThread;
    cudaLaunchAttribute at[1];
    at[0].id = cudaLaunchAttributeProgrammaticStreamSerialization;
    at[0].val.programmaticStreamSerializationAllowed = 1;
    cfg.attrs = at;
    cfg.numAttrs = pdl ? 1 : 0;
    cudaLaunchKernelEx(&cfg, kern, KArgs(args)...);
}

}

extern "C" void kernel_launch(void* const* d_in, const int* in_sizes, int n_in, void* d_out, int out_size) {
    (void)in_sizes; (void)n_in; (void)out_size;
    const __nv_bfloat16* x = (const __nv_bfloat16*)d_in[0];
    const void* wqkv = d_in[1];
    const void* wo = d_in[2];
    const void* wgate = d_in[4];
    const void* wup = d_in[5];
    const void* wdown = d_in[6];

    static EncodeFn encode = nullptr;
    static void *p_xn, *p_h, *p_o, *p_g;
    if (!encode) {
        void* fn = nullptr;
        cudaDriverEntryPointQueryResult qr;
        cudaGetDriverEntryPoint("cuTensorMapEncodeTiled", &fn, cudaEnableDefault, &qr);
        encode = (EncodeFn)fn;
        cudaGetSymbolAddress(&p_xn, g_xn);
        cudaGetSymbolAddress(&p_h, g_h);
        cudaGetSymbolAddress(&p_o, g_o);
        cudaGetSymbolAddress(&p_g, g_g);
        cudaFuncSetAttribute(k1_ln_qkv, cudaFuncAttributeMaxDynamicSharedMemorySize, K1_SMEM);
        cudaFuncSetAttribute(k2_attn_ffn, cudaFuncAttributeMaxDynamicSharedMemorySize, K2_SMEM);
        cudaFuncSetAttribute(k3_out, cudaFuncAttributeMaxDynamicSharedMemorySize, K3_SMEM);
    }
    const CUtensorMapSwizzle S128 = CU_TENSOR_MAP_SWIZZLE_128B, S64 = CU_TENSOR_MAP_SWIZZLE_64B;
    const CUtensorMap tm_x = make_map(encode, x, S, D, 128, 64, S128);
    const CUtensorMap tm_wqkv = make_map(encode, wqkv, D, 3 * D, 64, 64, S128);
    const CUtensorMap tm_xn = make_map(encode, p_xn, S, D, 128, 64, S128);
    const CUtensorMap tm_wg = make_map(encode, wgate, D, F, 64, 32, S64);
    const CUtensorMap tm_wu = make_map(encode, wup, D, F, 64, 32, S64);
    const CUtensorMap tm_wd = make_map(encode, wdown, F, D, 64, 64, S128);
    const CUtensorMap tm_h_ld = make_map(encode, p_h, S, F, 128, 64, S128);
    const CUtensorMap tm_h_st = make_map(encode, p_h, S, F, 128, 32, S64);
    const CUtensorMap tm_g = make_map(encode, p_g, S, D, 128, 64, S128);
    const CUtensorMap tm_o = make_map(encode, p_o, S, D, 128, 64, S128);
    const CUtensorMap tm_wo = make_map(encode, wo, D, D, 64, 64, S128);

    launch(k1_ln_qkv, 128, 288, K1_SMEM, false, tm_x, tm_wqkv);
    launch(k2_attn_ffn, 128, K2_THREADS, K2_SMEM, true, tm_xn, tm_wg, tm_wu, tm_wd, tm_h_ld, tm_h_st, tm_g, 0u);
    launch(k3_out, 128, 256, K3_SMEM, true, tm_o, tm_wo, x, (__nv_bfloat16*)d_out);
}
```

```cpp
#include <cuda_runtime.h>
#include <cuda_bf16.h>
#include <cuda.h>
#include <stdint.h>

namespace {

constexpr int S = 2048, D = 512, H = 32, F = 1792;

__device__ __align__(1024) uint4 g_q[H * 2 * S];
__device__ __align__(1024) uint4 g_kv[H * 16 * 4 * 128];
__device__ __align__(1024) __nv_bfloat16 g_xn[S * D];
__device__ __align__(1024) __nv_bfloat16 g_h[F * S];
__device__ __align__(1024) __nv_bfloat16 g_o[S * D];
__device__ __align__(1024) __nv_bfloat16 g_g[S * D];
__device__ unsigned g_flag[16 * 2];
#define TS(k, i)
#define TS_INIT()

__device__ __forceinline__ uint32_t smem_u32(const void* p) { return (uint32_t)__cvta_generic_to_shared(p); }
__device__ __forceinline__ void mbar_init(uint32_t b, uint32_t n) { asm volatile("mbarrier.init.shared::cta.b64 [%0], %1;" ::"r"(b), "r"(n)); }
__device__ __forceinline__ void mbar_expect(uint32_t b, uint32_t bytes) { asm volatile("mbarrier.arrive.expect_tx.shared::cta.b64 _, [%0], %1;" ::"r"(b), "r"(bytes) : "memory"); }
__device__ __forceinline__ void mbar_arrive(uint32_t b) { asm volatile("mbarrier.arrive.shared::cta.b64 _, [%0];" ::"r"(b) : "memory"); }
__device__ __forceinline__ void mbar_wait(uint32_t b, uint32_t parity) {
    asm volatile("{\n .reg .pred p;\n .reg .u32 c;\n"
                 " mbarrier.try_wait.parity.shared::cta.b64 p, [%0], %1;\n @p bra LAB_DONE;\n mov.u32 c, 0;\n"
                 "LAB_WAIT:\n mbarrier.try_wait.parity.shared::cta.b64 p, [%0], %1;\n @p bra LAB_DONE;\n"
                 " add.u32 c, c, 1;\n setp.lt.u32 p, c, 0x1000000;\n @p bra LAB_WAIT;\n trap;\n"
                 "LAB_DONE:\n}" ::"r"(b), "r"(parity) : "memory");
}
__device__ __forceinline__ bool mbar_test(uint32_t b, uint32_t parity) {
    uint32_t ok;
    asm volatile("{ .reg .pred p; mbarrier.test_wait.parity.shared::cta.b64 p, [%1], %2; selp.b32 %0, 1, 0, p; }" : "=r"(ok) : "r"(b), "r"(parity) : "memory");
    return ok;
}
__device__ __forceinline__ bool elect_one() {
    uint32_t p;
    asm volatile("{ .reg .pred p; elect.sync _|p, 0xffffffff; selp.b32 %0, 1, 0, p; }" : "=r"(p));
    return p;
}
__device__ __forceinline__ void fence_async_smem() { asm volatile("fence.proxy.async.shared::cta;" ::: "memory"); }
__device__ __forceinline__ void fence_bar_init() { asm volatile("fence.mbarrier_init.release.cluster;" ::: "memory"); }
__device__ __forceinline__ void named_bar(int id, int n) { asm volatile("bar.sync %0, %1;" ::"r"(id), "r"(n) : "memory"); }
__device__ __forceinline__ void named_arrive(int id, int n) { asm volatile("bar.arrive %0, %1;" ::"r"(id), "r"(n) : "memory"); }
__device__ __forceinline__ void pdl_wait() { asm volatile("griddepcontrol.wait;" ::: "memory"); }
__device__ __forceinline__ void pdl_launch() { asm volatile("griddepcontrol.launch_dependents;" ::: "memory"); }
__device__ __forceinline__ void tma_load(uint32_t dst, const CUtensorMap* m, int c0, int c1, uint32_t bar) {
    asm volatile("cp.async.bulk.tensor.2d.shared::cluster.global.mbarrier::complete_tx::bytes [%0], [%1, {%3, %4}], [%2];"
                 ::"r"(dst), "l"(m), "r"(bar), "r"(c0), "r"(c1) : "memory");
}
__device__ __forceinline__ void tma_store(const CUtensorMap* m, int c0, int c1, uint32_t src) {
    asm volatile("cp.async.bulk.tensor.2d.global.shared::cta.bulk_group [%0, {%2, %3}], [%1];" ::"l"(m), "r"(src), "r"(c0), "r"(c1) : "memory");
    asm volatile("cp.async.bulk.commit_group;" ::: "memory");
}
__device__ __forceinline__ void bulk_load(uint32_t dst, const void* src, uint32_t bytes, uint32_t bar) {
    asm volatile("cp.async.bulk.shared::cluster.global.mbarrier::complete_tx::bytes [%0], [%1], %2, [%3];" ::"r"(dst), "l"(src), "r"(bytes), "r"(bar) : "memory");
}
__device__ __forceinline__ void bulk_store(void* dst, uint32_t src, uint32_t bytes) {
    asm volatile("cp.async.bulk.global.shared::cta.bulk_group [%0], [%1], %2;" ::"l"(dst), "r"(src), "r"(bytes) : "memory");
}
__device__ __forceinline__ void l2_prefetch(const void* p, uint32_t bytes) { asm volatile("cp.async.bulk.prefetch.L2.global [%0], %1;" ::"l"(p), "r"(bytes) : "memory"); }
__device__ __forceinline__ void stsm_x4_t(uint32_t a, uint32_t r0, uint32_t r1, uint32_t r2, uint32_t r3) {
    asm volatile("stmatrix.sync.aligned.m8n8.x4.trans.shared.b16 [%0], {%1,%2,%3,%4};" ::"r"(a), "r"(r0), "r"(r1), "r"(r2), "r"(r3) : "memory");
}
#define WG_FENCE() asm volatile("wgmma.fence.sync.aligned;" ::: "memory")
#define WG_COMMIT() asm volatile("wgmma.commit_group.sync.aligned;" ::: "memory")
#define WG_WAIT(n) asm volatile("wgmma.wait_group.sync.aligned " #n ";" ::: "memory")
#define DESC_ADV(d, n) asm volatile("add.s64 %0, %0, %1;" : "+l"(d) : "l"((long long)(n)))
template <int N> __device__ __forceinline__ void keep(float (&a)[N]) {
#pragma unroll
    for (int i = 0; i < N; i++) asm volatile("" : "+f"(a[i])::"memory");
}
__device__ __forceinline__ uint64_t make_desc(uint32_t addr, uint32_t lbo, uint32_t sbo, uint32_t swz) {
    return (uint64_t)((addr & 0x3FFFF) >> 4) | ((uint64_t)(lbo >> 4) << 16) | ((uint64_t)(sbo >> 4) << 32) | ((uint64_t)swz << 62);
}
__device__ __forceinline__ float ex2(float x) { float y; asm("ex2.approx.ftz.f32 %0, %1;" : "=f"(y) : "f"(x)); return y; }
__device__ __forceinline__ float rcp(float x) { float y; asm("rcp.approx.ftz.f32 %0, %1;" : "=f"(y) : "f"(x)); return y; }
__device__ __forceinline__ uint32_t pack2(float lo, float hi) { uint32_t r; asm("cvt.rn.bf16x2.f32 %0, %1, %2;" : "=r"(r) : "f"(hi), "f"(lo)); return r; }
__device__ __forceinline__ float bf_lo(uint32_t v) { return __uint_as_float(v << 16); }
__device__ __forceinline__ float bf_hi(uint32_t v) { return __uint_as_float(v & 0xFFFF0000u); }

__device__ __forceinline__ void wgmma_n136_ta(float (&d)[68], uint64_t da, uint64_t db, int acc) {
    asm volatile("{ .reg .pred p; setp.ne.b32 p, %70, 0;\n"
      "wgmma.mma_async.sync.aligned.m64n136k16.f32.bf16.bf16 {%0,%1,%2,%3,%4,%5,%6,%7,%8,%9,%10,%11,%12,%13,%14,%15,%16,%17,%18,%19,%20,%21,%22,%23,%24,%25,%26,%27,%28,%29,%30,%31,%32,%33,%34,%35,%36,%37,%38,%39,%40,%41,%42,%43,%44,%45,%46,%47,%48,%49,%50,%51,%52,%53,%54,%55,%56,%57,%58,%59,%60,%61,%62,%63,%64,%65,%66,%67}, %68, %69, p, 1, 1, 1, 0; }"
      : "+f"(d[0]),"+f"(d[1]),"+f"(d[2]),"+f"(d[3]),"+f"(d[4]),"+f"(d[5]),"+f"(d[6]),"+f"(d[7]),"+f"(d[8]),"+f"(d[9]),"+f"(d[10]),"+f"(d[11]),"+f"(d[12]),"+f"(d[13]),"+f"(d[14]),"+f"(d[15]),"+f"(d[16]),"+f"(d[17]),"+f"(d[18]),"+f"(d[19]),"+f"(d[20]),"+f"(d[21]),"+f"(d[22]),"+f"(d[23]),"+f"(d[24]),"+f"(d[25]),"+f"(d[26]),"+f"(d[27]),"+f"(d[28]),"+f"(d[29]),"+f"(d[30]),"+f"(d[31]),"+f"(d[32]),"+f"(d[33]),"+f"(d[34]),"+f"(d[35]),"+f"(d[36]),"+f"(d[37]),"+f"(d[38]),"+f"(d[39]),"+f"(d[40]),"+f"(d[41]),"+f"(d[42]),"+f"(d[43]),"+f"(d[44]),"+f"(d[45]),"+f"(d[46]),"+f"(d[47]),"+f"(d[48]),"+f"(d[49]),"+f"(d[50]),"+f"(d[51]),"+f"(d[52]),"+f"(d[53]),"+f"(d[54]),"+f"(d[55]),"+f"(d[56]),"+f"(d[57]),"+f"(d[58]),"+f"(d[59]),"+f"(d[60]),"+f"(d[61]),"+f"(d[62]),"+f"(d[63]),"+f"(d[64]),"+f"(d[65]),"+f"(d[66]),"+f"(d[67])
      : "l"(da), "l"(db), "r"(acc));
}
__device__ __forceinline__ void wgmma_n128_ta(float (&d)[64], uint64_t da, uint64_t db, int acc) {
    asm volatile("{ .reg .pred p; setp.ne.b32 p, %66, 0;\n"
      "wgmma.mma_async.sync.aligned.m64n128k16.f32.bf16.bf16 {%0,%1,%2,%3,%4,%5,%6,%7,%8,%9,%10,%11,%12,%13,%14,%15,%16,%17,%18,%19,%20,%21,%22,%23,%24,%25,%26,%27,%28,%29,%30,%31,%32,%33,%34,%35,%36,%37,%38,%39,%40,%41,%42,%43,%44,%45,%46,%47,%48,%49,%50,%51,%52,%53,%54,%55,%56,%57,%58,%59,%60,%61,%62,%63}, %64, %65, p, 1, 1, 1, 0; }"
      : "+f"(d[0]),"+f"(d[1]),"+f"(d[2]),"+f"(d[3]),"+f"(d[4]),"+f"(d[5]),"+f"(d[6]),"+f"(d[7]),"+f"(d[8]),"+f"(d[9]),"+f"(d[10]),"+f"(d[11]),"+f"(d[12]),"+f"(d[13]),"+f"(d[14]),"+f"(d[15]),"+f"(d[16]),"+f"(d[17]),"+f"(d[18]),"+f"(d[19]),"+f"(d[20]),"+f"(d[21]),"+f"(d[22]),"+f"(d[23]),"+f"(d[24]),"+f"(d[25]),"+f"(d[26]),"+f"(d[27]),"+f"(d[28]),"+f"(d[29]),"+f"(d[30]),"+f"(d[31]),"+f"(d[32]),"+f"(d[33]),"+f"(d[34]),"+f"(d[35]),"+f"(d[36]),"+f"(d[37]),"+f"(d[38]),"+f"(d[39]),"+f"(d[40]),"+f"(d[41]),"+f"(d[42]),"+f"(d[43]),"+f"(d[44]),"+f"(d[45]),"+f"(d[46]),"+f"(d[47]),"+f"(d[48]),"+f"(d[49]),"+f"(d[50]),"+f"(d[51]),"+f"(d[52]),"+f"(d[53]),"+f"(d[54]),"+f"(d[55]),"+f"(d[56]),"+f"(d[57]),"+f"(d[58]),"+f"(d[59]),"+f"(d[60]),"+f"(d[61]),"+f"(d[62]),"+f"(d[63])
      : "l"(da), "l"(db), "r"(acc));
}
__device__ __forceinline__ void wgmma_n128_tab(float (&d)[64], uint64_t da, uint64_t db, int acc) {
    asm volatile("{ .reg .pred p; setp.ne.b32 p, %66, 0;\n"
      "wgmma.mma_async.sync.aligned.m64n128k16.f32.bf16.bf16 {%0,%1,%2,%3,%4,%5,%6,%7,%8,%9,%10,%11,%12,%13,%14,%15,%16,%17,%18,%19,%20,%21,%22,%23,%24,%25,%26,%27,%28,%29,%30,%31,%32,%33,%34,%35,%36,%37,%38,%39,%40,%41,%42,%43,%44,%45,%46,%47,%48,%49,%50,%51,%52,%53,%54,%55,%56,%57,%58,%59,%60,%61,%62,%63}, %64, %65, p, 1, 1, 1, 1; }"
      : "+f"(d[0]),"+f"(d[1]),"+f"(d[2]),"+f"(d[3]),"+f"(d[4]),"+f"(d[5]),"+f"(d[6]),"+f"(d[7]),"+f"(d[8]),"+f"(d[9]),"+f"(d[10]),"+f"(d[11]),"+f"(d[12]),"+f"(d[13]),"+f"(d[14]),"+f"(d[15]),"+f"(d[16]),"+f"(d[17]),"+f"(d[18]),"+f"(d[19]),"+f"(d[20]),"+f"(d[21]),"+f"(d[22]),"+f"(d[23]),"+f"(d[24]),"+f"(d[25]),"+f"(d[26]),"+f"(d[27]),"+f"(d[28]),"+f"(d[29]),"+f"(d[30]),"+f"(d[31]),"+f"(d[32]),"+f"(d[33]),"+f"(d[34]),"+f"(d[35]),"+f"(d[36]),"+f"(d[37]),"+f"(d[38]),"+f"(d[39]),"+f"(d[40]),"+f"(d[41]),"+f"(d[42]),"+f"(d[43]),"+f"(d[44]),"+f"(d[45]),"+f"(d[46]),"+f"(d[47]),"+f"(d[48]),"+f"(d[49]),"+f"(d[50]),"+f"(d[51]),"+f"(d[52]),"+f"(d[53]),"+f"(d[54]),"+f"(d[55]),"+f"(d[56]),"+f"(d[57]),"+f"(d[58]),"+f"(d[59]),"+f"(d[60]),"+f"(d[61]),"+f"(d[62]),"+f"(d[63])
      : "l"(da), "l"(db), "r"(acc));
}
__device__ __forceinline__ void wgmma_n64_tb(float (&d)[32], uint64_t da, uint64_t db, int acc) {
    asm volatile("{ .reg .pred p; setp.ne.b32 p, %34, 0;\n"
      "wgmma.mma_async.sync.aligned.m64n64k16.f32.bf16.bf16 {%0,%1,%2,%3,%4,%5,%6,%7,%8,%9,%10,%11,%12,%13,%14,%15,%16,%17,%18,%19,%20,%21,%22,%23,%24,%25,%26,%27,%28,%29,%30,%31}, %32, %33, p, 1, 1, 0, 1; }"
      : "+f"(d[0]),"+f"(d[1]),"+f"(d[2]),"+f"(d[3]),"+f"(d[4]),"+f"(d[5]),"+f"(d[6]),"+f"(d[7]),"+f"(d[8]),"+f"(d[9]),"+f"(d[10]),"+f"(d[11]),"+f"(d[12]),"+f"(d[13]),"+f"(d[14]),"+f"(d[15]),"+f"(d[16]),"+f"(d[17]),"+f"(d[18]),"+f"(d[19]),"+f"(d[20]),"+f"(d[21]),"+f"(d[22]),"+f"(d[23]),"+f"(d[24]),"+f"(d[25]),"+f"(d[26]),"+f"(d[27]),"+f"(d[28]),"+f"(d[29]),"+f"(d[30]),"+f"(d[31])
      : "l"(da), "l"(db), "r"(acc));
}
__device__ __forceinline__ void wgmma_qk(float (&d)[32], const uint32_t* a, uint64_t db) {
    asm volatile("wgmma.mma_async.sync.aligned.m64n64k16.f32.bf16.bf16 {%0,%1,%2,%3,%4,%5,%6,%7,%8,%9,%10,%11,%12,%13,%14,%15,%16,%17,%18,%19,%20,%21,%22,%23,%24,%25,%26,%27,%28,%29,%30,%31}, {%32,%33,%34,%35}, %36, 0, 1, 1, 0;"
      : "=f"(d[0]),"=f"(d[1]),"=f"(d[2]),"=f"(d[3]),"=f"(d[4]),"=f"(d[5]),"=f"(d[6]),"=f"(d[7]),"=f"(d[8]),"=f"(d[9]),"=f"(d[10]),"=f"(d[11]),"=f"(d[12]),"=f"(d[13]),"=f"(d[14]),"=f"(d[15]),"=f"(d[16]),"=f"(d[17]),"=f"(d[18]),"=f"(d[19]),"=f"(d[20]),"=f"(d[21]),"=f"(d[22]),"=f"(d[23]),"=f"(d[24]),"=f"(d[25]),"=f"(d[26]),"=f"(d[27]),"=f"(d[28]),"=f"(d[29]),"=f"(d[30]),"=f"(d[31])
      : "r"(a[0]), "r"(a[1]), "r"(a[2]), "r"(a[3]), "l"(db));
}
__device__ __forceinline__ void wgmma_pv(float (&d)[12], const uint32_t* a, uint64_t db) {
    asm volatile("wgmma.mma_async.sync.aligned.m64n24k16.f32.bf16.bf16 {%0,%1,%2,%3,%4,%5,%6,%7,%8,%9,%10,%11}, {%12,%13,%14,%15}, %16, 1, 1, 1, 1;"
      : "+f"(d[0]),"+f"(d[1]),"+f"(d[2]),"+f"(d[3]),"+f"(d[4]),"+f"(d[5]),"+f"(d[6]),"+f"(d[7]),"+f"(d[8]),"+f"(d[9]),"+f"(d[10]),"+f"(d[11])
      : "r"(a[0]), "r"(a[1]), "r"(a[2]), "r"(a[3]), "l"(db));
}

constexpr int K1_XB = 17408;
constexpr int K1_X = 0, K1_W = 8 * K1_XB, K1_STAGE = 24576, K1_NST = 3;
constexpr int K1_PART = K1_W + K1_NST * K1_STAGE, K1_TAB = K1_PART + 3 * 128 * 8, K1_BAR = K1_TAB + 128 * 8, K1_SMEM = K1_BAR + 128;
constexpr float Q_SCALE = 0.25f * 1.4426950408889634f;

__global__ void __launch_bounds__(416, 1)
k1_ln_qkv(const __grid_constant__ CUtensorMap tm_x, const __grid_constant__ CUtensorMap tm_wqkv, const uint8_t* __restrict__ w_qkv,
          const uint8_t* __restrict__ w_gate, const uint8_t* __restrict__ w_up, const uint8_t* __restrict__ w_down, const uint8_t* __restrict__ w_o) {
    extern __shared__ __align__(1024) uint8_t smem[];
    const uint32_t sb = smem_u32(smem);
    const uint32_t bar_x = sb + K1_BAR, bar_full = bar_x + 64, bar_empty = bar_full + 8 * K1_NST;
    const int tid = threadIdx.x, lane = tid & 31;
    const int warp = __shfl_sync(~0u, tid >> 5, 0);
    const int rt = blockIdx.x >> 3, ct = blockIdx.x & 7;
    TS_INIT();
    if (tid == 32) l2_prefetch(w_qkv + blockIdx.x * (D * 3 * D * 2 / 128), D * 3 * D * 2 / 128);
    if (tid == 0) {
        for (int i = 0; i < 8; i++) mbar_init(bar_x + 8 * i, 1);
        for (int i = 0; i < K1_NST; i++) { mbar_init(bar_full + 8 * i, 1); mbar_init(bar_empty + 8 * i, 12); }
        fence_bar_init();
    }
    if (blockIdx.x == 0 && tid < 32) g_flag[tid] = 0;
    __syncthreads();
    pdl_launch();
    if (warp == 12) {
        auto load_w = [&](int kb, int st) {
            mbar_expect(bar_full + 8 * st, K1_STAGE);
            for (int b = 0; b < 3; b++) tma_load(sb + K1_W + st * K1_STAGE + b * 8192, &tm_wqkv, ct * 192 + b * 64, kb * 64, bar_full + 8 * st);
        };
        if (elect_one()) {
            for (int kb = 0; kb < 8; kb++) {
                mbar_expect(bar_x + 8 * kb, 16384);
                tma_load(sb + K1_X + kb * K1_XB, &tm_x, kb * 64, rt * 128, bar_x + 8 * kb);
                if (kb < K1_NST) load_w(kb, kb);
            }
            for (int kb = K1_NST; kb < 8; kb++) {
                const int st = kb % K1_NST;
                mbar_wait(bar_empty + 8 * st, (kb / K1_NST - 1) & 1);
                load_w(kb, st);
            }
            l2_prefetch(w_gate + blockIdx.x * (D * F * 2 / 128), D * F * 2 / 128);
            l2_prefetch(w_up + blockIdx.x * (D * F * 2 / 128), D * F * 2 / 128);
            l2_prefetch(w_down + blockIdx.x * (D * F * 2 / 128), D * F * 2 / 128);
            l2_prefetch(w_o + blockIdx.x * (D * D * 2 / 128), D * D * 2 / 128);
        }
        return;
    }
    const int wg = warp >> 2, w = warp & 3;
    for (int i = tid; i < 8 * 64; i += 384) {
        const uint32_t v = ((i & 63) < 8) ? 0x3F803F80u : 0u;
        *(uint4*)(smem + K1_X + (i >> 6) * K1_XB + 16384 + (i & 63) * 16) = make_uint4(v, v, v, v);
    }
    fence_async_smem();
    named_bar(1, 384);
    float acc[68];
    const int tok = tid & 127;
    float shift = 0.f, s1 = 0.f, s2 = 0.f;
    {
        uint64_t da = make_desc(sb + K1_W + wg * 8192, 16, 1024, 1), db = make_desc(sb + K1_X, 16, 1024, 1);
#pragma unroll
        for (int kb = 0; kb < 8; kb++) {
            const int st = kb % K1_NST;
            mbar_wait(bar_x + 8 * kb, 0);
            mbar_wait(bar_full + 8 * st, (kb / K1_NST) & 1);
            WG_FENCE();
#pragma unroll
            for (int k = 0; k < 4; k++) {
                wgmma_n136_ta(acc, da, db, kb | k);
                DESC_ADV(da, k < 3 ? 128 : (st < K1_NST - 1 ? (K1_STAGE >> 4) - 384 : -((K1_NST - 1) * (K1_STAGE >> 4) + 384)));
                DESC_ADV(db, k < 3 ? 2 : (K1_XB >> 4) - 6);
            }
            WG_COMMIT();
            if (kb == 0) shift = bf_lo(*(const uint32_t*)(smem + K1_X + tok * 128 + ((tok & 7) << 4)));
            if (kb % 3 == wg) {
                const uint8_t* row = smem + K1_X + kb * K1_XB + tok * 128;
#pragma unroll
                for (int c = 0; c < 8; c++) {
                    const uint4 v = *(const uint4*)(row + ((c ^ (tok & 7)) << 4));
                    const uint32_t vv[4] = {v.x, v.y, v.z, v.w};
#pragma unroll
                    for (int e = 0; e < 4; e++) {
                        const float a = bf_lo(vv[e]) - shift, b = bf_hi(vv[e]) - shift;
                        s1 += a + b;
                        s2 = fmaf(a, a, fmaf(b, b, s2));
                    }
                }
            }
            if (kb > 0 && kb < 8 - K1_NST + 1) {
                WG_WAIT(1);
                if (lane == 0) mbar_arrive(bar_empty + 8 * ((kb - 1) % K1_NST));
            }
        }
        if (tid == 0) TS(0, 0);
        *(float2*)(smem + K1_PART + (wg * 128 + tok) * 8) = make_float2(s1, s2);
        named_bar(1, 384);
        if (wg == 0) {
            const float2 p0 = *(const float2*)(smem + K1_PART + tok * 8), p1 = *(const float2*)(smem + K1_PART + (128 + tok) * 8),
                         p2 = *(const float2*)(smem + K1_PART + (256 + tok) * 8);
            const float m = (p0.x + p1.x + p2.x) * (1.f / D);
            const float var = fmaxf((p0.y + p1.y + p2.y) * (1.f / D) - m * m, 0.f);
            *(float2*)(smem + K1_TAB + tok * 8) = make_float2(shift + m, rsqrtf(var + 1e-5f));
        }
        WG_WAIT(0);
        keep(acc);
        named_bar(1, 384);
        if (tid == 0) TS(0, 1);
    }
    if (tid == 0) TS(0, 3);
    {
        const int col = ct * 192 + wg * 64 + w * 16;
        const int which = col >> 9, head = (col >> 4) & 31, t = lane & 3;
        const float cs0 = __shfl_sync(~0u, acc[64], lane & ~3), cs1 = __shfl_sync(~0u, acc[66], lane & ~3);
        const float sc = which == 0 ? Q_SCALE : 1.f;
        const uint32_t stg = sb + K1_W + warp * 4096;
#pragma unroll
        for (int jp = 0; jp < 8; jp++) {
            uint32_t r[4];
#pragma unroll
            for (int jj = 0; jj < 2; jj++) {
                const int j = 2 * jp + jj;
                const float4 st = *(const float4*)(smem + K1_TAB + (8 * j + 2 * t) * 8);
                const float a0 = st.y * sc, a1 = st.w * sc;
                r[2 * jj] = pack2(fmaf(-st.x, cs0, acc[4 * j]) * a0, fmaf(-st.z, cs0, acc[4 * j + 1]) * a1);
                r[2 * jj + 1] = pack2(fmaf(-st.x, cs1, acc[4 * j + 2]) * a0, fmaf(-st.z, cs1, acc[4 * j + 3]) * a1);
            }
            const int mi = lane >> 3;
            stsm_x4_t(stg + (mi & 1) * 2048 + (8 * (2 * jp + (mi >> 1)) + (lane & 7)) * 16, r[0], r[1], r[2], r[3]);
        }
        if (tid == 0) TS(0, 4);
        fence_async_smem();
        __syncwarp();
        if (tid == 0) TS(0, 5);
        if (elect_one()) {
            uint4* dst0;
            uint4* dst1;
            if (which == 0) { dst0 = g_q + head * 2 * S + rt * 128; dst1 = dst0 + S; }
            else { dst0 = g_kv + ((head * 16 + rt) * 4 + (which - 1) * 2) * 128; dst1 = dst0 + 128; }
            bulk_store(dst0, stg, 2048);
            bulk_store(dst1, stg + 2048, 2048);
            asm volatile("cp.async.bulk.commit_group;" ::: "memory");
        }
    }
    {
        for (int r = ct * 16 + warp; r < ct * 16 + 16; r += 12) {
            const float2 st = *(const float2*)(smem + K1_TAB + r * 8);
            const uint8_t* p = smem + K1_X + (lane >> 3) * K1_XB + r * 128 + (((lane & 7) ^ (r & 7)) << 4);
            uint4* g = (uint4*)(g_xn + (size_t)(rt * 128 + r) * D);
#pragma unroll
            for (int hh = 0; hh < 2; hh++) {
                const uint4 v = *(const uint4*)(p + hh * 4 * K1_XB);
                uint4 o;
                o.x = pack2((bf_lo(v.x) - st.x) * st.y, (bf_hi(v.x) - st.x) * st.y);
                o.y = pack2((bf_lo(v.y) - st.x) * st.y, (bf_hi(v.y) - st.x) * st.y);
                o.z = pack2((bf_lo(v.z) - st.x) * st.y, (bf_hi(v.z) - st.x) * st.y);
                o.w = pack2((bf_lo(v.w) - st.x) * st.y, (bf_hi(v.w) - st.x) * st.y);
                g[hh * 32 + lane] = o;
            }
        }
    }
    asm volatile("cp.async.bulk.wait_group.read 0;" ::: "memory");
    if (tid == 0) TS(0, 2);
}

constexpr int K2_WNST = 2;
constexpr int K2_X = 0, K2_W = 131072, K2_XCH = K2_W + K2_WNST * 16384, K2_RING = K2_XCH + 8192, K2_RSTAGE = 10240, K2_RNST = 4;
constexpr int K2_BAR = K2_RING + K2_RNST * K2_RSTAGE, K2_SMEM = K2_BAR + 512;
constexpr int K2_DSTAGE = 24576, K2_DNST = 4;
constexpr int K2_THREADS = 640;
#define FFN_BATCH 4

#define POLY_MASK 0xDADA
#define REFOFF 80.f
constexpr float REF_OFFSET = REFOFF;
constexpr float POLY_LOG2K = -0.052214f;

struct PolyC { uint32_t one, e2; };
__device__ __forceinline__ uint32_t exp2_soft(float a, float b, float bz, const PolyC& c) {
    float ra, rb;
    asm("fma.rn.sat.f32 %0, %1, 0f00000080, %2;" : "=f"(ra) : "f"(a), "f"(bz));
    asm("fma.rn.sat.f32 %0, %1, 0f00000080, %2;" : "=f"(rb) : "f"(b), "f"(bz));
    uint32_t W, G, d, Y;
    asm("cvt.pack.sat.s16.s32 %0, %1, %2;" : "=r"(W) : "r"(__float_as_uint(rb)), "r"(__float_as_uint(ra)));
    asm("lop3.b32 %0, %1, 0x007F007F, %2, 0xEA;" : "=r"(G) : "r"(W), "r"(c.one));
    asm("fma.rn.bf16x2 %0, %1, %2, %3;" : "=r"(d) : "r"(G), "r"(c.e2), "r"(0xBF27BF27u));
    asm("fma.rn.bf16x2 %0, %1, %2, %3;" : "=r"(d) : "r"(G), "r"(d), "r"(0x3EC83EC8u));
    asm("fma.rn.bf16x2 %0, %1, %2, %1;" : "=r"(Y) : "r"(W), "r"(d));
    return Y;
}
__device__ __forceinline__ void softmax_step(const float (&s)[32], uint32_t (&p)[16], float nm0, float nm1, float bz0, float bz1, const PolyC& c) {
#pragma unroll
    for (int i = 0; i < 16; i++)
        if (!((POLY_MASK >> i) & 1)) { const float nm = (i & 1) ? nm1 : nm0; p[i] = pack2(ex2(s[2 * i] + nm), ex2(s[2 * i + 1] + nm)); }
#pragma unroll
    for (int i = 0; i < 16; i++)
        if ((POLY_MASK >> i) & 1) p[i] = exp2_soft(s[2 * i], s[2 * i + 1], (i & 1) ? bz1 : bz0, c);
}
__device__ __forceinline__ void mma16816(float (&d)[4], const uint32_t* a, uint32_t b0, uint32_t b1) {
    asm volatile("mma.sync.aligned.m16n8k16.row.col.f32.bf16.bf16.f32 {%0,%1,%2,%3},{%4,%5,%6,%7},{%8,%9},{%0,%1,%2,%3};"
                 : "+f"(d[0]), "+f"(d[1]), "+f"(d[2]), "+f"(d[3]) : "r"(a[0]), "r"(a[1]), "r"(a[2]), "r"(a[3]), "r"(b0), "r"(b1));
}
__device__ __forceinline__ void attn_rows_true_max(const uint32_t (&qf)[4], const uint4* gkv, __nv_bfloat16* orow, int lane) {
    const int g = lane >> 2, t = lane & 3;
    auto row = [&](int plane, int key) { return gkv + ((key >> 7) * 4 + plane) * 128 + (key & 127); };
    auto kw = [&](int plane, int key) { return ((const uint32_t*)row(plane, key))[t]; };
    auto vw = [&](int plane, int key) { return ((const uint16_t*)row(plane, key))[g] | ((uint32_t)((const uint16_t*)row(plane, key + 1))[g] << 16); };
    float m0 = -INFINITY, m1 = -INFINITY;
#pragma unroll 1
    for (int kb = 0; kb < S / 8; kb++) {
        float s[4] = {0.f, 0.f, 0.f, 0.f};
        mma16816(s, qf, kw(0, kb * 8 + g), kw(1, kb * 8 + g));
        m0 = fmaxf(m0, fmaxf(s[0], s[1]));
        m1 = fmaxf(m1, fmaxf(s[2], s[3]));
    }
    m0 = fmaxf(m0, __shfl_xor_sync(~0u, m0, 1)); m0 = fmaxf(m0, __shfl_xor_sync(~0u, m0, 2));
    m1 = fmaxf(m1, __shfl_xor_sync(~0u, m1, 1)); m1 = fmaxf(m1, __shfl_xor_sync(~0u, m1, 2));
    float o0[4] = {0.f, 0.f, 0.f, 0.f}, o1[4] = {0.f, 0.f, 0.f, 0.f}, l0 = 0.f, l1 = 0.f;
#pragma unroll 1
    for (int kb = 0; kb < S / 16; kb++) {
        float sa[4] = {0.f, 0.f, 0.f, 0.f}, sc[4] = {0.f, 0.f, 0.f, 0.f};
        mma16816(sa, qf, kw(0, kb * 16 + g), kw(1, kb * 16 + g));
        mma16816(sc, qf, kw(0, kb * 16 + 8 + g), kw(1, kb * 16 + 8 + g));
        uint32_t p[4];
        p[0] = pack2(ex2(sa[0] - m0), ex2(sa[1] - m0));
        p[1] = pack2(ex2(sa[2] - m1), ex2(sa[3] - m1));
        p[2] = pack2(ex2(sc[0] - m0), ex2(sc[1] - m0));
        p[3] = pack2(ex2(sc[2] - m1), ex2(sc[3] - m1));
        l0 += bf_lo(p[0]) + bf_hi(p[0]) + bf_lo(p[2]) + bf_hi(p[2]);
        l1 += bf_lo(p[1]) + bf_hi(p[1]) + bf_lo(p[3]) + bf_hi(p[3]);
        const int key = kb * 16 + 2 * t;
        mma16816(o0, p, vw(2, key), vw(2, key + 8));
        mma16816(o1, p, vw(3, key), vw(3, key + 8));
    }
    l0 += __shfl_xor_sync(~0u, l0, 1); l0 += __shfl_xor_sync(~0u, l0, 2);
    l1 += __shfl_xor_sync(~0u, l1, 1); l1 += __shfl_xor_sync(~0u, l1, 2);
    const float i0 = 1.f / l0, i1 = 1.f / l1;
    *(uint32_t*)(orow + 2 * t) = pack2(o0[0] * i0, o0[1] * i0);
    *(uint32_t*)(orow + 8 + 2 * t) = pack2(o1[0] * i0, o1[1] * i0);
    *(uint32_t*)(orow + 8 * D + 2 * t) = pack2(o0[2] * i1, o0[3] * i1);
    *(uint32_t*)(orow + 8 * D + 8 + 2 * t) = pack2(o1[2] * i1, o1[3] * i1);
}

__global__ void __launch_bounds__(K2_THREADS, 1)
k2_attn_ffn(const __grid_constant__ CUtensorMap tm_xn, const __grid_constant__ CUtensorMap tm_wg, const __grid_constant__ CUtensorMap tm_wu,
            const __grid_constant__ CUtensorMap tm_wd, const __grid_constant__ CUtensorMap tm_h, const __grid_constant__ CUtensorMap tm_g, uint32_t zero) {
    extern __shared__ __align__(1024) uint8_t smem[];
    const uint32_t sb = smem_u32(smem);
    const uint32_t bar_rfull = sb + K2_BAR, bar_rempty = bar_rfull + 32;
    const uint32_t bar_x = bar_rempty + 32, bar_wfull = bar_x + 64, bar_dfull = bar_wfull + 8 * K2_WNST;
    const int tid = threadIdx.x, lane = tid & 31;
    const int wg = __shfl_sync(~0u, tid >> 7, 0);
    TS_INIT();
    if (tid == 0) {
        for (int i = 0; i < 4; i++) { mbar_init(bar_rfull + 8 * i, 1); mbar_init(bar_rempty + 8 * i, 16); }
        for (int i = 0; i < K2_WNST; i++) mbar_init(bar_wfull + 8 * i, 1);
        for (int i = 0; i < K2_DNST; i++) mbar_init(bar_dfull + 8 * i, 1);
        for (int i = 0; i < 8; i++) mbar_init(bar_x + 8 * i, 1);
        fence_bar_init();
    }
    if (tid < K2_RNST * 128) *(uint4*)(smem + K2_RING + (tid >> 7) * K2_RSTAGE + 8192 + (tid & 127) * 16) = make_uint4(0x00003F80u, 0, 0, 0);
    fence_async_smem();
    __syncthreads();
    pdl_launch();

    if (wg < 4) {
        pdl_wait();
        if (tid == 0) TS(1, 0);
        const int head = blockIdx.x >> 2, part = blockIdx.x & 3;
        const int warp4 = (tid >> 5) & 3;
        const uint4* gq = g_q + head * 2 * S;
        PolyC pc;
        pc.one = 0x3F803F80u ^ zero;
        pc.e2 = 0x3E623E62u ^ zero;
        const uint64_t dk0 = make_desc(sb + K2_RING, 2048, 128, 0), dv0 = make_desc(sb + K2_RING + 4096, 128, 2048, 0);
        constexpr int RS = K2_RSTAGE >> 4;
        uint32_t qf[4];
        auto load_q = [&](int rnd) {
            const uint32_t* qp = (const uint32_t*)(gq + part * 512 + (rnd * 4 + wg) * 64 + warp4 * 16 + (lane >> 2)) + (lane & 3);
            qf[0] = qp[0]; qf[1] = qp[32]; qf[2] = qp[S * 4]; qf[3] = qp[S * 4 + 32];
        };
        load_q(0);
#pragma unroll 1
        for (int rnd = 0; rnd < 2; rnd++) {
            const int row0 = part * 512 + (rnd * 4 + wg) * 64 + warp4 * 16;
            float s[32], o[12];
            uint32_t p[16];
            mbar_wait(bar_rfull, 0);
            WG_FENCE(); wgmma_qk(s, qf, dk0); WG_COMMIT(); WG_WAIT(0); keep(s);
            if (wg == 0 && rnd == 0) TS(1, 1);
            float m0 = -INFINITY, m1 = -INFINITY;
#pragma unroll
            for (int i = 0; i < 32; i += 4) { m0 = fmaxf(m0, fmaxf(s[i], s[i + 1])); m1 = fmaxf(m1, fmaxf(s[i + 2], s[i + 3])); }
            m0 = fmaxf(m0, __shfl_xor_sync(~0u, m0, 1)); m0 = fmaxf(m0, __shfl_xor_sync(~0u, m0, 2));
            m1 = fmaxf(m1, __shfl_xor_sync(~0u, m1, 1)); m1 = fmaxf(m1, __shfl_xor_sync(~0u, m1, 2));
            m0 = ceilf(m0) + REF_OFFSET; m1 = ceilf(m1) + REF_OFFSET;
            float nm0 = POLY_LOG2K - m0, nm1 = POLY_LOG2K - m1;
            float bz0 = __fmul_rn(__fmul_rn(127.0f - m0, 0x1p-71f), 0x1p-71f), bz1 = __fmul_rn(__fmul_rn(127.0f - m1, 0x1p-71f), 0x1p-71f);
            asm volatile("" : "+f"(nm0), "+f"(nm1), "+f"(bz0), "+f"(bz1));
#pragma unroll
            for (int i = 0; i < 12; i++) o[i] = 0.f;
#pragma unroll 1
            for (int it = 0; it < 8; it++) {
                const int s0 = (it & 1) * 2;
                const uint32_t par = (it >> 1) & 1;
                uint64_t dk = dk0 + s0 * RS, dv = dv0 + s0 * RS;
#pragma unroll
                for (int u = 0; u < 4; u++) {
                    if (u == 0 || u == 2) mbar_wait(bar_rfull + 8 * (s0 + (u >> 1)), par);
                    WG_FENCE(); wgmma_qk(s, qf, dk); WG_COMMIT();
                    if (u == 1) DESC_ADV(dk, 576); else DESC_ADV(dk, 64);
                    WG_WAIT(0); keep(s);
                    if (u == 2 && lane == 0) mbar_arrive(bar_rempty + 8 * s0);
                    if (u == 0 && it > 0 && lane == 0) mbar_arrive(bar_rempty + 8 * ((s0 + 3) & 3));
                    softmax_step(s, p, nm0, nm1, bz0, bz1, pc);
                    WG_FENCE();
                    wgmma_pv(o, p, dv); DESC_ADV(dv, 16);
                    wgmma_pv(o, p + 4, dv); DESC_ADV(dv, 16);
                    wgmma_pv(o, p + 8, dv); DESC_ADV(dv, 16);
                    wgmma_pv(o, p + 12, dv);
                    if (u == 1) DESC_ADV(dv, 528); else DESC_ADV(dv, 16);
                    WG_COMMIT();
                }
            }
            uint32_t qo[4] = {qf[0], qf[1], qf[2], qf[3]};
            if (rnd == 0) load_q(1);
            WG_WAIT(0);
            keep(o);
            if (lane == 0) mbar_arrive(bar_rempty + 8 * 3);
            const float l0 = __shfl_sync(~0u, o[8], lane & ~3), l1 = __shfl_sync(~0u, o[10], lane & ~3);
            bool bad = !(l0 < 0x1p120f) || !(l1 < 0x1p120f);
#pragma unroll
            for (int i = 0; i < 8; i++) bad = bad || !(fabsf(o[i]) < INFINITY);
            __nv_bfloat16* orow = g_o + (size_t)(row0 + (lane >> 2)) * D + head * 16;
            if (__any_sync(~0u, bad)) {
                attn_rows_true_max(qo, g_kv + head * 8192, orow, lane);
            } else {
                const float i0 = rcp(l0), i1 = rcp(l1);
                const int t = lane & 3;
                *(uint32_t*)(orow + 2 * t) = pack2(o[0] * i0, o[1] * i0);
                *(uint32_t*)(orow + 8 + 2 * t) = pack2(o[4] * i0, o[5] * i0);
                *(uint32_t*)(orow + 8 * D + 2 * t) = pack2(o[2] * i1, o[3] * i1);
                *(uint32_t*)(orow + 8 * D + 8 + 2 * t) = pack2(o[6] * i1, o[7] * i1);
            }
            TS(1, 2 + rnd * 4 + wg);
        }
    } else {
        const int rt = blockIdx.x >> 3, ct = blockIdx.x & 7;
        const int w = __shfl_sync(~0u, (tid >> 5) & 3, 0);
        float acc[64];
        const uint4* gkv = g_kv + (blockIdx.x >> 2) * 8192;
        int rn = 0;
        auto ring_issue = [&]() {
            if (elect_one()) {
                mbar_expect(bar_rfull + 8 * (rn & 3), 8192);
                bulk_load(sb + K2_RING + (rn & 3) * K2_RSTAGE, gkv + (rn & 15) * 512, 8192, bar_rfull + 8 * (rn & 3));
            }
            rn++;
        };
        auto ring_ready = [&]() { return mbar_test(bar_rempty + 8 * (rn & 3), ((rn >> 2) & 1) ^ 1); };
        auto ring_poll = [&]() { if (w == 1 && rn < 32 && ring_ready()) ring_issue(); };
        auto ring_drain = [&]() { if (w == 1) while (rn < 32) { mbar_wait(bar_rempty + 8 * (rn & 3), ((rn >> 2) & 1) ^ 1); ring_issue(); } };
        auto load_w = [&](int n, int stage) {
            if (elect_one()) {
                const int col = ct * 224 + (n >> 2) * 32, k = (n & 3) * 128;
                mbar_expect(bar_wfull + 8 * stage, 16384);
                tma_load(sb + K2_W + stage * 16384, &tm_wg, col, k, bar_wfull + 8 * stage);
                tma_load(sb + K2_W + stage * 16384 + 8192, &tm_wu, col, k, bar_wfull + 8 * stage);
            }
        };
        auto released = [&](int id) { if (w == 0) named_bar(id, 128); else named_arrive(id, 128); };
        if (w == 0) { load_w(0, 0); load_w(1, 1); }
        pdl_wait();
        if (w == 1) { ring_issue(); ring_issue(); ring_issue(); ring_issue(); }
        if (w == 0 && elect_one()) {
            for (int kb = 0; kb < 8; kb++) { mbar_expect(bar_x + 8 * kb, 16384); tma_load(sb + K2_X + kb * 16384, &tm_xn, kb * 64, rt * 128, bar_x + 8 * kb); }
        }
        {
            uint64_t da = make_desc(sb + K2_W, 8192, 512, 2), db = make_desc(sb + K2_X, 16, 1024, 1);
            uint32_t mine[16];
            auto finish_tile = [&](int tile) {
                named_bar(2, 128);
                if (tile == 4 && w == 3 && lane == 0) asm volatile("red.release.gpu.global.add.u32 [%0], 1;" ::"l"(&g_flag[rt * 2]) : "memory");
                const uint4* xr = (const uint4*)(smem + K2_XCH) + (w ^ 2) * 128 + lane;
#pragma unroll
                for (int i = 0; i < 4; i++) {
                    const uint4 r = xr[i * 32];
                    const uint32_t rr[4] = {r.x, r.y, r.z, r.w};
#pragma unroll
                    for (int e = 0; e < 4; e++) asm("mul.rn.bf16x2 %0, %0, %1;" : "+r"(mine[4 * i + e]) : "r"(rr[e]));
                }
                const int g = lane >> 2, t = lane & 3, odd = t & 1;
                __nv_bfloat16* hrow = g_h + (size_t)(ct * 224 + tile * 32 + (w & 1) * 16 + g) * S + rt * 128 + (w >> 1) * 64 + odd * 8 + (t >> 1) * 4;
#pragma unroll
                for (int jp = 0; jp < 4; jp++)
#pragma unroll
                    for (int r = 0; r < 2; r++) {
                        const uint32_t a = mine[4 * jp + r], b = mine[4 * jp + 2 + r];
                        const uint32_t got = __shfl_xor_sync(~0u, odd ? a : b, 1);
                        *(uint2*)(hrow + (size_t)r * 8 * S + jp * 16) = odd ? make_uint2(got, b) : make_uint2(a, got);
                    }
            };
#pragma unroll 1
            for (int tile = 0; tile < 7; tile++) {
#pragma unroll
                for (int kd = 0; kd < 4; kd++) {
                    if (tile == 0) { mbar_wait(bar_x + 16 * kd, 0); mbar_wait(bar_x + 16 * kd + 8, 0); }
                    mbar_wait(bar_wfull + 8 * (kd & 1), kd >> 1);
                    WG_FENCE();
#pragma unroll
                    for (int k = 0; k < 8; k++) {
                        wgmma_n128_ta(acc, da, db, kd | k);
                        DESC_ADV(da, k < 7 ? 64 : ((kd & 1) == 0 ? 1024 - 448 : -(1024 + 448)));
                        DESC_ADV(db, (k & 3) < 3 ? 2 : (k == 3 || kd < 3 ? 1024 - 6 : -(7 * 1024 + 6)));
                        if (k == 1 && kd > 0) {
                            WG_COMMIT();
                            WG_WAIT(1);
                            released(3 + (kd & 1));
                            if (w == 0 && (kd < 3 || tile < 6)) load_w(tile * 4 + kd + 1, (kd - 1) & 1);
                            WG_FENCE();
                        }
                    }
                    WG_COMMIT();
                    if (kd == 0 && tile > 0) finish_tile(tile - 1);
                    ring_poll();
                }
                WG_WAIT(0);
                released(3);
                if (w == 0 && tile < 6) load_w(tile * 4 + 5, 1);
                keep(acc);
                uint4* xs = (uint4*)(smem + K2_XCH) + w * 128 + lane;
                if (w < 2) {
#pragma unroll
                    for (int i = 0; i < 16; i++) mine[i] = pack2(acc[2 * i], acc[2 * i + 1]);
#pragma unroll
                    for (int i = 0; i < 4; i++)
                        xs[i * 32] = make_uint4(pack2(acc[32 + 8 * i], acc[33 + 8 * i]), pack2(acc[34 + 8 * i], acc[35 + 8 * i]),
                                                pack2(acc[36 + 8 * i], acc[37 + 8 * i]), pack2(acc[38 + 8 * i], acc[39 + 8 * i]));
                } else {
#pragma unroll
                    for (int i = 0; i < 16; i++) mine[i] = pack2(acc[32 + 2 * i], acc[33 + 2 * i]);
#pragma unroll
                    for (int i = 0; i < 4; i++)
                        xs[i * 32] = make_uint4(pack2(acc[8 * i], acc[1 + 8 * i]), pack2(acc[2 + 8 * i], acc[3 + 8 * i]),
                                                pack2(acc[4 + 8 * i], acc[5 + 8 * i]), pack2(acc[6 + 8 * i], acc[7 + 8 * i]));
                }
            }
            finish_tile(6);
        }
        TS(1, 10);
        named_bar(2, 128);
        if (w == 3 && lane == 0) asm volatile("red.release.gpu.global.add.u32 [%0], 1;" ::"l"(&g_flag[rt * 2 + 1]) : "memory");
        auto wait_flag = [&](int which) {
            if (lane == 0) {
                unsigned v;
                int spin = 0;
                do {
                    asm volatile("ld.acquire.gpu.global.u32 %0, [%1];" : "=r"(v) : "l"(&g_flag[rt * 2 + which]) : "memory");
                    if (v < 8) __nanosleep(64);
                } while (v < 8 && ++spin < (1 << 22));
                if (v < 8) __trap();
            }
            __syncwarp();
            asm volatile("fence.proxy.async.global;" ::: "memory");
        };
        auto load_d = [&](int i, int stage) {
            if (i == 0) wait_flag(0);
            if (i == 12) wait_flag(1);
            if (elect_one()) {
                const int j = (i < 12) ? 7 * (i / 3) + ((0x410 >> (4 * (i % 3))) & 7) : 7 * ((i - 12) >> 2) + ((0x6532 >> (4 * ((i - 12) & 3))) & 7);
                const uint32_t dst = sb + K2_X + stage * K2_DSTAGE;
                mbar_expect(bar_dfull + 8 * stage, K2_DSTAGE);
                tma_load(dst, &tm_wd, ct * 64, j * 64, bar_dfull + 8 * stage);
                tma_load(dst + 8192, &tm_h, rt * 128, j * 64, bar_dfull + 8 * stage);
                tma_load(dst + 16384, &tm_h, rt * 128 + 64, j * 64, bar_dfull + 8 * stage);
            }
        };
        if (w == 0) { load_d(0, 0); load_d(1, 1); load_d(2, 2); load_d(3, 3); }
        {
            uint64_t da = make_desc(sb + K2_X, 16, 1024, 1), db = make_desc(sb + K2_X + 8192, 8192, 1024, 1);
            {
                int spin = 0;
                while (!mbar_test(bar_dfull, 0)) { ring_poll(); if (++spin > (1 << 26)) __trap(); }
            }
            TS(1, 11);
#pragma unroll 1
            for (int it = 0; it < 7; it++) {
#pragma unroll
                for (int q = 0; q < 4; q++) {
                    constexpr int DS = K2_DSTAGE >> 4;
                    mbar_wait(bar_dfull + 8 * q, it & 1);
                    WG_FENCE();
#pragma unroll
                    for (int k = 0; k < 4; k++) {
                        wgmma_n128_tab(acc, da, db, it | q | k);
                        const int adv = k < 3 ? 128 : (q < 3 ? DS - 384 : -(3 * DS + 384));
                        DESC_ADV(da, adv); DESC_ADV(db, adv);
                        if (k == 1 && (q > 0 || it > 0)) {
                            WG_COMMIT();
                            WG_WAIT(1);
                            released(3 + (q & 1));
                            const int n = it * 4 + q + 3;
                            if (w == 0 && n < 28) load_d(n, (q + 3) & 3);
                            WG_FENCE();
                        }
                    }
                    WG_COMMIT();
                    if (q & 1) ring_poll();
                }
            }
            WG_WAIT(0);
            keep(acc);
            TS(1, 12);
#pragma unroll
            for (int i = 0; i < 8; i++) {
                uint32_t gv[4];
#pragma unroll
                for (int e = 0; e < 4; e++) {
                    const float y0 = acc[8 * i + 2 * e], y1 = acc[8 * i + 2 * e + 1];
                    gv[e] = pack2(__fdividef(y0, 1.f + __expf(-y0)), __fdividef(y1, 1.f + __expf(-y1)));
                }
                const int mi = lane >> 3;
                const int tok = 8 * (2 * i + (mi >> 1)) + (lane & 7);
                const int chunk = 2 * w + (mi & 1);
                stsm_x4_t(sb + K2_W + tok * 128 + ((chunk ^ (tok & 7)) << 4), gv[0], gv[1], gv[2], gv[3]);
            }
            fence_async_smem();
            named_bar(2, 128);
            if (w == 0 && elect_one()) {
                tma_store(&tm_g, ct * 64, rt * 128, sb + K2_W);
                asm volatile("cp.async.bulk.wait_group.read 0;" ::: "memory");
            }
            TS(1, 13);
        }
        ring_drain();
    }
}

constexpr int K3_A = 0, K3_B = 65536, K3_BAR = K3_B + 131072, K3_SMEM = K3_BAR + 128;

__global__ void __launch_bounds__(256, 1)
k3_out(const __grid_constant__ CUtensorMap tm_o, const __grid_constant__ CUtensorMap tm_wo, const __nv_bfloat16* __restrict__ x, __nv_bfloat16* __restrict__ out) {
    extern __shared__ __align__(1024) uint8_t smem[];
    const uint32_t sb = smem_u32(smem);
    const uint32_t bar_a = sb + K3_BAR, bar_b = bar_a + 64;
    const int tid = threadIdx.x, lane = tid & 31;
    const int warp = __shfl_sync(~0u, tid >> 5, 0);
    const int rt = blockIdx.x >> 2, ct = blockIdx.x & 3;
    TS_INIT();
    if (warp == 0 && elect_one()) {
        for (int i = 0; i < 8; i++) mbar_init(bar_a + 8 * i, 1);
        mbar_init(bar_b, 1);
        fence_bar_init();
        mbar_expect(bar_b, 131072);
        for (int kb = 0; kb < 8; kb++)
            for (int hh = 0; hh < 2; hh++) tma_load(sb + K3_B + hh * 65536 + kb * 8192, &tm_wo, ct * 128 + hh * 64, kb * 64, bar_b);
    }
    const int wg = warp >> 2, g = lane >> 2, t = lane & 3;
    const size_t e0 = (size_t)(rt * 64 + (warp & 3) * 16 + g) * D + ct * 128 + wg * 64 + 2 * t;
    uint32_t xv[16], gv[16];
#pragma unroll
    for (int j = 0; j < 8; j++) { xv[2 * j] = *(const uint32_t*)(x + e0 + 8 * j); xv[2 * j + 1] = *(const uint32_t*)(x + e0 + 8 * D + 8 * j); }
    __syncthreads();
    pdl_wait();
    if (tid == 0) TS(2, 0);
    if (warp == 0 && elect_one()) {
        for (int kb = 0; kb < 8; kb++) { mbar_expect(bar_a + 8 * kb, 8192); tma_load(sb + K3_A + kb * 8192, &tm_o, kb * 64, rt * 64, bar_a + 8 * kb); }
    }
#pragma unroll
    for (int j = 0; j < 8; j++) { gv[2 * j] = *(const uint32_t*)(g_g + e0 + 8 * j); gv[2 * j + 1] = *(const uint32_t*)(g_g + e0 + 8 * D + 8 * j); }
    float acc[32];
    uint64_t da = make_desc(sb + K3_A, 16, 1024, 1), db = make_desc(sb + K3_B + wg * 65536, 16, 1024, 1);
    mbar_wait(bar_b, 0);
#pragma unroll
    for (int kb = 0; kb < 8; kb++) {
        mbar_wait(bar_a + 8 * kb, 0);
        WG_FENCE();
#pragma unroll
        for (int k = 0; k < 4; k++) {
            wgmma_n64_tb(acc, da, db, kb | k);
            DESC_ADV(da, k < 3 ? 2 : 512 - 6);
            DESC_ADV(db, 128);
        }
        WG_COMMIT();
    }
    WG_WAIT(0);
    keep(acc);
    if (tid == 0) TS(2, 1);
#pragma unroll
    for (int j = 0; j < 8; j++) {
        *(uint32_t*)(out + e0 + 8 * j) = pack2(fmaf(acc[4 * j], bf_lo(gv[2 * j]), bf_lo(xv[2 * j])), fmaf(acc[4 * j + 1], bf_hi(gv[2 * j]), bf_hi(xv[2 * j])));
        *(uint32_t*)(out + e0 + 8 * D + 8 * j) =
            pack2(fmaf(acc[4 * j + 2], bf_lo(gv[2 * j + 1]), bf_lo(xv[2 * j + 1])), fmaf(acc[4 * j + 3], bf_hi(gv[2 * j + 1]), bf_hi(xv[2 * j + 1])));
    }
}

typedef CUresult (*EncodeFn)(CUtensorMap*, CUtensorMapDataType, cuuint32_t, void*, const cuuint64_t*, const cuuint64_t*, const cuuint32_t*,
                             const cuuint32_t*, CUtensorMapInterleave, CUtensorMapSwizzle, CUtensorMapL2promotion, CUtensorMapFloatOOBfill);

CUtensorMap make_map(EncodeFn fn, const void* ptr, int rows, int cols, int box_rows, int box_cols, CUtensorMapSwizzle swz) {
    CUtensorMap m;
    const cuuint64_t dims[2] = {(cuuint64_t)cols, (cuuint64_t)rows};
    const cuuint64_t strides[1] = {(cuuint64_t)cols * 2};
    const cuuint32_t box[2] = {(cuuint32_t)box_cols, (cuuint32_t)box_rows};
    const cuuint32_t estr[2] = {1, 1};
    fn(&m, CU_TENSOR_MAP_DATA_TYPE_BFLOAT16, 2, const_cast<void*>(ptr), dims, strides, box, estr, CU_TENSOR_MAP_INTERLEAVE_NONE, swz,
       CU_TENSOR_MAP_L2_PROMOTION_L2_256B, CU_TENSOR_MAP_FLOAT_OOB_FILL_NONE);
    return m;
}

template <typename... KArgs, typename... Args>
void launch(void (*kern)(KArgs...), int grid, int block, int smem, bool pdl, Args... args) {
    cudaLaunchConfig_t cfg = {};
    cfg.gridDim = dim3(grid);
    cfg.blockDim = dim3(block);
    cfg.dynamicSmemBytes = smem;
    cfg.stream = cudaStreamPerThread;
    cudaLaunchAttribute at[1];
    at[0].id = cudaLaunchAttributeProgrammaticStreamSerialization;
    at[0].val.programmaticStreamSerializationAllowed = 1;
    cfg.attrs = at;
    cfg.numAttrs = pdl ? 1 : 0;
    cudaLaunchKernelEx(&cfg, kern, KArgs(args)...);
}

}

extern "C" void kernel_launch(void* const* d_in, const int* in_sizes, int n_in, void* d_out, int out_size) {
    (void)in_sizes; (void)n_in; (void)out_size;
    const __nv_bfloat16* x = (const __nv_bfloat16*)d_in[0];
    const void* wqkv = d_in[1];
    const void* wo = d_in[2];
    const void* wgate = d_in[4];
    const void* wup = d_in[5];
    const void* wdown = d_in[6];

    static EncodeFn encode = nullptr;
    static void *p_xn, *p_h, *p_o, *p_g;
    if (!encode) {
        void* fn = nullptr;
        cudaDriverEntryPointQueryResult qr;
        cudaGetDriverEntryPoint("cuTensorMapEncodeTiled", &fn, cudaEnableDefault, &qr);
        encode = (EncodeFn)fn;
        cudaGetSymbolAddress(&p_xn, g_xn);
        cudaGetSymbolAddress(&p_h, g_h);
        cudaGetSymbolAddress(&p_o, g_o);
        cudaGetSymbolAddress(&p_g, g_g);
        cudaFuncSetAttribute(k1_ln_qkv, cudaFuncAttributeMaxDynamicSharedMemorySize, K1_SMEM);
        cudaFuncSetAttribute(k2_attn_ffn, cudaFuncAttributeMaxDynamicSharedMemorySize, K2_SMEM);
        cudaFuncSetAttribute(k3_out, cudaFuncAttributeMaxDynamicSharedMemorySize, K3_SMEM);
    }
    const CUtensorMapSwizzle S128 = CU_TENSOR_MAP_SWIZZLE_128B, S64 = CU_TENSOR_MAP_SWIZZLE_64B;
    const CUtensorMap tm_x = make_map(encode, x, S, D, 128, 64, S128);
    const CUtensorMap tm_wqkv = make_map(encode, wqkv, D, 3 * D, 64, 64, S128);
    const CUtensorMap tm_xn = make_map(encode, p_xn, S, D, 128, 64, S128);
    const CUtensorMap tm_wg = make_map(encode, wgate, D, F, 128, 32, S64);
    const CUtensorMap tm_wu = make_map(encode, wup, D, F, 128, 32, S64);
    const CUtensorMap tm_wd = make_map(encode, wdown, F, D, 64, 64, S128);
    const CUtensorMap tm_h = make_map(encode, p_h, F, S, 64, 64, S128);
    const CUtensorMap tm_g = make_map(encode, p_g, S, D, 128, 64, S128);
    const CUtensorMap tm_o = make_map(encode, p_o, S, D, 64, 64, S128);
    const CUtensorMap tm_wo = make_map(encode, wo, D, D, 64, 64, S128);

    launch(k1_ln_qkv, 128, 416, K1_SMEM, false, tm_x, tm_wqkv, (const uint8_t*)wqkv, (const uint8_t*)wgate, (const uint8_t*)wup, (const uint8_t*)wdown, (const uint8_t*)wo);
    launch(k2_attn_ffn, 128, K2_THREADS, K2_SMEM, true, tm_xn, tm_wg, tm_wu, tm_wd, tm_h, tm_g, 0u);
    launch(k3_out, 128, 256, K3_SMEM, true, tm_o, tm_wo, x, (__nv_bfloat16*)d_out);
}
```

```cpp
#include <cuda_runtime.h>
#include <cuda_bf16.h>
#include <cuda.h>
#include <stdint.h>

namespace {

constexpr int S = 2048, D = 512, H = 32, F = 1792;

__device__ __align__(1024) uint4 g_q[H * 2 * S];
__device__ __align__(1024) uint4 g_kv[H * 16 * 4 * 128];
__device__ __align__(1024) __nv_bfloat16 g_xn[S * D];
__device__ __align__(1024) __nv_bfloat16 g_h[F * S];
__device__ __align__(1024) __nv_bfloat16 g_o[S * D];
__device__ __align__(1024) __nv_bfloat16 g_g[S * D];
__device__ unsigned g_flag[16 * 2];
#define TS(k, i)
#define GT(k, i)
#define TS_INIT()

__device__ __forceinline__ uint32_t smem_u32(const void* p) { return (uint32_t)__cvta_generic_to_shared(p); }
__device__ __forceinline__ void mbar_init(uint32_t b, uint32_t n) { asm volatile("mbarrier.init.shared::cta.b64 [%0], %1;" ::"r"(b), "r"(n)); }
__device__ __forceinline__ void mbar_expect(uint32_t b, uint32_t bytes) { asm volatile("mbarrier.arrive.expect_tx.shared::cta.b64 _, [%0], %1;" ::"r"(b), "r"(bytes) : "memory"); }
__device__ __forceinline__ void mbar_arrive(uint32_t b) { asm volatile("mbarrier.arrive.shared::cta.b64 _, [%0];" ::"r"(b) : "memory"); }
__device__ __forceinline__ void mbar_wait(uint32_t b, uint32_t parity) {
    asm volatile("{\n .reg .pred p;\n .reg .u32 c;\n"
                 " mbarrier.try_wait.parity.shared::cta.b64 p, [%0], %1;\n @p bra LAB_DONE;\n mov.u32 c, 0;\n"
                 "LAB_WAIT:\n mbarrier.try_wait.parity.shared::cta.b64 p, [%0], %1;\n @p bra LAB_DONE;\n"
                 " add.u32 c, c, 1;\n setp.lt.u32 p, c, 0x1000000;\n @p bra LAB_WAIT;\n trap;\n"
                 "LAB_DONE:\n}" ::"r"(b), "r"(parity) : "memory");
}
__device__ __forceinline__ bool mbar_test(uint32_t b, uint32_t parity) {
    uint32_t ok;
    asm volatile("{ .reg .pred p; mbarrier.test_wait.parity.shared::cta.b64 p, [%1], %2; selp.b32 %0, 1, 0, p; }" : "=r"(ok) : "r"(b), "r"(parity) : "memory");
    return ok;
}
__device__ __forceinline__ bool elect_one() {
    uint32_t p;
    asm volatile("{ .reg .pred p; elect.sync _|p, 0xffffffff; selp.b32 %0, 1, 0, p; }" : "=r"(p));
    return p;
}
__device__ __forceinline__ void fence_async_smem() { asm volatile("fence.proxy.async.shared::cta;" ::: "memory"); }
__device__ __forceinline__ void fence_bar_init() { asm volatile("fence.mbarrier_init.release.cluster;" ::: "memory"); }
__device__ __forceinline__ void named_bar(int id, int n) { asm volatile("bar.sync %0, %1;" ::"r"(id), "r"(n) : "memory"); }
__device__ __forceinline__ void named_arrive(int id, int n) { asm volatile("bar.arrive %0, %1;" ::"r"(id), "r"(n) : "memory"); }
__device__ __forceinline__ void pdl_wait() { asm volatile("griddepcontrol.wait;" ::: "memory"); }
__device__ __forceinline__ void pdl_launch() { asm volatile("griddepcontrol.launch_dependents;" ::: "memory"); }
__device__ __forceinline__ void tma_load(uint32_t dst, const CUtensorMap* m, int c0, int c1, uint32_t bar) {
    asm volatile("cp.async.bulk.tensor.2d.shared::cluster.global.mbarrier::complete_tx::bytes [%0], [%1, {%3, %4}], [%2];"
                 ::"r"(dst), "l"(m), "r"(bar), "r"(c0), "r"(c1) : "memory");
}
__device__ __forceinline__ void tma_store(const CUtensorMap* m, int c0, int c1, uint32_t src) {
    asm volatile("cp.async.bulk.tensor.2d.global.shared::cta.bulk_group [%0, {%2, %3}], [%1];" ::"l"(m), "r"(src), "r"(c0), "r"(c1) : "memory");
    asm volatile("cp.async.bulk.commit_group;" ::: "memory");
}
__device__ __forceinline__ void tma_load_mc(uint32_t dst, const CUtensorMap* m, int c0, int c1, uint32_t bar, uint16_t mask) {
    asm volatile("cp.async.bulk.tensor.2d.shared::cluster.global.mbarrier::complete_tx::bytes.multicast::cluster [%0], [%1, {%3, %4}], [%2], %5;"
                 ::"r"(dst), "l"(m), "r"(bar), "r"(c0), "r"(c1), "h"(mask) : "memory");
}
__device__ __forceinline__ void cluster_sync() { asm volatile("barrier.cluster.arrive.release.aligned;\n barrier.cluster.wait.acquire.aligned;" ::: "memory"); }
__device__ __forceinline__ void bulk_load(uint32_t dst, const void* src, uint32_t bytes, uint32_t bar) {
    asm volatile("cp.async.bulk.shared::cluster.global.mbarrier::complete_tx::bytes [%0], [%1], %2, [%3];" ::"r"(dst), "l"(src), "r"(bytes), "r"(bar) : "memory");
}
__device__ __forceinline__ void prefetch_map(const CUtensorMap* m) { asm volatile("prefetch.tensormap [%0];" ::"l"(m) : "memory"); }
__device__ __forceinline__ void l2_prefetch(const void* p, uint32_t bytes) { asm volatile("cp.async.bulk.prefetch.L2.global [%0], %1;" ::"l"(p), "r"(bytes) : "memory"); }
__device__ __forceinline__ void stsm_x4_t(uint32_t a, uint32_t r0, uint32_t r1, uint32_t r2, uint32_t r3) {
    asm volatile("stmatrix.sync.aligned.m8n8.x4.trans.shared.b16 [%0], {%1,%2,%3,%4};" ::"r"(a), "r"(r0), "r"(r1), "r"(r2), "r"(r3) : "memory");
}
#define WG_FENCE() asm volatile("wgmma.fence.sync.aligned;" ::: "memory")
#define WG_COMMIT() asm volatile("wgmma.commit_group.sync.aligned;" ::: "memory")
#define WG_WAIT(n) asm volatile("wgmma.wait_group.sync.aligned " #n ";" ::: "memory")
#define DESC_ADV(d, n) asm volatile("add.s64 %0, %0, %1;" : "+l"(d) : "l"((long long)(n)))
template <int N> __device__ __forceinline__ void keep(float (&a)[N]) {
#pragma unroll
    for (int i = 0; i < N; i++) asm volatile("" : "+f"(a[i])::"memory");
}
__device__ __forceinline__ uint64_t make_desc(uint32_t addr, uint32_t lbo, uint32_t sbo, uint32_t swz) {
    return (uint64_t)((addr & 0x3FFFF) >> 4) | ((uint64_t)(lbo >> 4) << 16) | ((uint64_t)(sbo >> 4) << 32) | ((uint64_t)swz << 62);
}
__device__ __forceinline__ float ex2(float x) { float y; asm("ex2.approx.ftz.f32 %0, %1;" : "=f"(y) : "f"(x)); return y; }
__device__ __forceinline__ float rcp(float x) { float y; asm("rcp.approx.ftz.f32 %0, %1;" : "=f"(y) : "f"(x)); return y; }
__device__ __forceinline__ uint32_t pack2(float lo, float hi) { uint32_t r; asm("cvt.rn.bf16x2.f32 %0, %1, %2;" : "=r"(r) : "f"(hi), "f"(lo)); return r; }
__device__ __forceinline__ float bf_lo(uint32_t v) { return __uint_as_float(v << 16); }
__device__ __forceinline__ float bf_hi(uint32_t v) { return __uint_as_float(v & 0xFFFF0000u); }

__device__ __forceinline__ void wgmma_n136_ta(float (&d)[68], uint64_t da, uint64_t db, int acc) {
    asm volatile("{ .reg .pred p; setp.ne.b32 p, %70, 0;\n"
      "wgmma.mma_async.sync.aligned.m64n136k16.f32.bf16.bf16 {%0,%1,%2,%3,%4,%5,%6,%7,%8,%9,%10,%11,%12,%13,%14,%15,%16,%17,%18,%19,%20,%21,%22,%23,%24,%25,%26,%27,%28,%29,%30,%31,%32,%33,%34,%35,%36,%37,%38,%39,%40,%41,%42,%43,%44,%45,%46,%47,%48,%49,%50,%51,%52,%53,%54,%55,%56,%57,%58,%59,%60,%61,%62,%63,%64,%65,%66,%67}, %68, %69, p, 1, 1, 1, 0; }"
      : "+f"(d[0]),"+f"(d[1]),"+f"(d[2]),"+f"(d[3]),"+f"(d[4]),"+f"(d[5]),"+f"(d[6]),"+f"(d[7]),"+f"(d[8]),"+f"(d[9]),"+f"(d[10]),"+f"(d[11]),"+f"(d[12]),"+f"(d[13]),"+f"(d[14]),"+f"(d[15]),"+f"(d[16]),"+f"(d[17]),"+f"(d[18]),"+f"(d[19]),"+f"(d[20]),"+f"(d[21]),"+f"(d[22]),"+f"(d[23]),"+f"(d[24]),"+f"(d[25]),"+f"(d[26]),"+f"(d[27]),"+f"(d[28]),"+f"(d[29]),"+f"(d[30]),"+f"(d[31]),"+f"(d[32]),"+f"(d[33]),"+f"(d[34]),"+f"(d[35]),"+f"(d[36]),"+f"(d[37]),"+f"(d[38]),"+f"(d[39]),"+f"(d[40]),"+f"(d[41]),"+f"(d[42]),"+f"(d[43]),"+f"(d[44]),"+f"(d[45]),"+f"(d[46]),"+f"(d[47]),"+f"(d[48]),"+f"(d[49]),"+f"(d[50]),"+f"(d[51]),"+f"(d[52]),"+f"(d[53]),"+f"(d[54]),"+f"(d[55]),"+f"(d[56]),"+f"(d[57]),"+f"(d[58]),"+f"(d[59]),"+f"(d[60]),"+f"(d[61]),"+f"(d[62]),"+f"(d[63]),"+f"(d[64]),"+f"(d[65]),"+f"(d[66]),"+f"(d[67])
      : "l"(da), "l"(db), "r"(acc));
}
__device__ __forceinline__ void wgmma_n128_ta(float (&d)[64], uint64_t da, uint64_t db, int acc) {
    asm volatile("{ .reg .pred p; setp.ne.b32 p, %66, 0;\n"
      "wgmma.mma_async.sync.aligned.m64n128k16.f32.bf16.bf16 {%0,%1,%2,%3,%4,%5,%6,%7,%8,%9,%10,%11,%12,%13,%14,%15,%16,%17,%18,%19,%20,%21,%22,%23,%24,%25,%26,%27,%28,%29,%30,%31,%32,%33,%34,%35,%36,%37,%38,%39,%40,%41,%42,%43,%44,%45,%46,%47,%48,%49,%50,%51,%52,%53,%54,%55,%56,%57,%58,%59,%60,%61,%62,%63}, %64, %65, p, 1, 1, 1, 0; }"
      : "+f"(d[0]),"+f"(d[1]),"+f"(d[2]),"+f"(d[3]),"+f"(d[4]),"+f"(d[5]),"+f"(d[6]),"+f"(d[7]),"+f"(d[8]),"+f"(d[9]),"+f"(d[10]),"+f"(d[11]),"+f"(d[12]),"+f"(d[13]),"+f"(d[14]),"+f"(d[15]),"+f"(d[16]),"+f"(d[17]),"+f"(d[18]),"+f"(d[19]),"+f"(d[20]),"+f"(d[21]),"+f"(d[22]),"+f"(d[23]),"+f"(d[24]),"+f"(d[25]),"+f"(d[26]),"+f"(d[27]),"+f"(d[28]),"+f"(d[29]),"+f"(d[30]),"+f"(d[31]),"+f"(d[32]),"+f"(d[33]),"+f"(d[34]),"+f"(d[35]),"+f"(d[36]),"+f"(d[37]),"+f"(d[38]),"+f"(d[39]),"+f"(d[40]),"+f"(d[41]),"+f"(d[42]),"+f"(d[43]),"+f"(d[44]),"+f"(d[45]),"+f"(d[46]),"+f"(d[47]),"+f"(d[48]),"+f"(d[49]),"+f"(d[50]),"+f"(d[51]),"+f"(d[52]),"+f"(d[53]),"+f"(d[54]),"+f"(d[55]),"+f"(d[56]),"+f"(d[57]),"+f"(d[58]),"+f"(d[59]),"+f"(d[60]),"+f"(d[61]),"+f"(d[62]),"+f"(d[63])
      : "l"(da), "l"(db), "r"(acc));
}
__device__ __forceinline__ void wgmma_n128_tab(float (&d)[64], uint64_t da, uint64_t db, int acc) {
    asm volatile("{ .reg .pred p; setp.ne.b32 p, %66, 0;\n"
      "wgmma.mma_async.sync.aligned.m64n128k16.f32.bf16.bf16 {%0,%1,%2,%3,%4,%5,%6,%7,%8,%9,%10,%11,%12,%13,%14,%15,%16,%17,%18,%19,%20,%21,%22,%23,%24,%25,%26,%27,%28,%29,%30,%31,%32,%33,%34,%35,%36,%37,%38,%39,%40,%41,%42,%43,%44,%45,%46,%47,%48,%49,%50,%51,%52,%53,%54,%55,%56,%57,%58,%59,%60,%61,%62,%63}, %64, %65, p, 1, 1, 1, 1; }"
      : "+f"(d[0]),"+f"(d[1]),"+f"(d[2]),"+f"(d[3]),"+f"(d[4]),"+f"(d[5]),"+f"(d[6]),"+f"(d[7]),"+f"(d[8]),"+f"(d[9]),"+f"(d[10]),"+f"(d[11]),"+f"(d[12]),"+f"(d[13]),"+f"(d[14]),"+f"(d[15]),"+f"(d[16]),"+f"(d[17]),"+f"(d[18]),"+f"(d[19]),"+f"(d[20]),"+f"(d[21]),"+f"(d[22]),"+f"(d[23]),"+f"(d[24]),"+f"(d[25]),"+f"(d[26]),"+f"(d[27]),"+f"(d[28]),"+f"(d[29]),"+f"(d[30]),"+f"(d[31]),"+f"(d[32]),"+f"(d[33]),"+f"(d[34]),"+f"(d[35]),"+f"(d[36]),"+f"(d[37]),"+f"(d[38]),"+f"(d[39]),"+f"(d[40]),"+f"(d[41]),"+f"(d[42]),"+f"(d[43]),"+f"(d[44]),"+f"(d[45]),"+f"(d[46]),"+f"(d[47]),"+f"(d[48]),"+f"(d[49]),"+f"(d[50]),"+f"(d[51]),"+f"(d[52]),"+f"(d[53]),"+f"(d[54]),"+f"(d[55]),"+f"(d[56]),"+f"(d[57]),"+f"(d[58]),"+f"(d[59]),"+f"(d[60]),"+f"(d[61]),"+f"(d[62]),"+f"(d[63])
      : "l"(da), "l"(db), "r"(acc));
}
__device__ __forceinline__ void wgmma_n64_tb(float (&d)[32], uint64_t da, uint64_t db, int acc) {
    asm volatile("{ .reg .pred p; setp.ne.b32 p, %34, 0;\n"
      "wgmma.mma_async.sync.aligned.m64n64k16.f32.bf16.bf16 {%0,%1,%2,%3,%4,%5,%6,%7,%8,%9,%10,%11,%12,%13,%14,%15,%16,%17,%18,%19,%20,%21,%22,%23,%24,%25,%26,%27,%28,%29,%30,%31}, %32, %33, p, 1, 1, 0, 1; }"
      : "+f"(d[0]),"+f"(d[1]),"+f"(d[2]),"+f"(d[3]),"+f"(d[4]),"+f"(d[5]),"+f"(d[6]),"+f"(d[7]),"+f"(d[8]),"+f"(d[9]),"+f"(d[10]),"+f"(d[11]),"+f"(d[12]),"+f"(d[13]),"+f"(d[14]),"+f"(d[15]),"+f"(d[16]),"+f"(d[17]),"+f"(d[18]),"+f"(d[19]),"+f"(d[20]),"+f"(d[21]),"+f"(d[22]),"+f"(d[23]),"+f"(d[24]),"+f"(d[25]),"+f"(d[26]),"+f"(d[27]),"+f"(d[28]),"+f"(d[29]),"+f"(d[30]),"+f"(d[31])
      : "l"(da), "l"(db), "r"(acc));
}
__device__ __forceinline__ void wgmma_qk(float (&d)[32], const uint32_t* a, uint64_t db) {
    asm volatile("wgmma.mma_async.sync.aligned.m64n64k16.f32.bf16.bf16 {%0,%1,%2,%3,%4,%5,%6,%7,%8,%9,%10,%11,%12,%13,%14,%15,%16,%17,%18,%19,%20,%21,%22,%23,%24,%25,%26,%27,%28,%29,%30,%31}, {%32,%33,%34,%35}, %36, 0, 1, 1, 0;"
      : "=f"(d[0]),"=f"(d[1]),"=f"(d[2]),"=f"(d[3]),"=f"(d[4]),"=f"(d[5]),"=f"(d[6]),"=f"(d[7]),"=f"(d[8]),"=f"(d[9]),"=f"(d[10]),"=f"(d[11]),"=f"(d[12]),"=f"(d[13]),"=f"(d[14]),"=f"(d[15]),"=f"(d[16]),"=f"(d[17]),"=f"(d[18]),"=f"(d[19]),"=f"(d[20]),"=f"(d[21]),"=f"(d[22]),"=f"(d[23]),"=f"(d[24]),"=f"(d[25]),"=f"(d[26]),"=f"(d[27]),"=f"(d[28]),"=f"(d[29]),"=f"(d[30]),"=f"(d[31])
      : "r"(a[0]), "r"(a[1]), "r"(a[2]), "r"(a[3]), "l"(db));
}
__device__ __forceinline__ void wgmma_pv(float (&d)[12], const uint32_t* a, uint64_t db) {
    asm volatile("wgmma.mma_async.sync.aligned.m64n24k16.f32.bf16.bf16 {%0,%1,%2,%3,%4,%5,%6,%7,%8,%9,%10,%11}, {%12,%13,%14,%15}, %16, 1, 1, 1, 1;"
      : "+f"(d[0]),"+f"(d[1]),"+f"(d[2]),"+f"(d[3]),"+f"(d[4]),"+f"(d[5]),"+f"(d[6]),"+f"(d[7]),"+f"(d[8]),"+f"(d[9]),"+f"(d[10]),"+f"(d[11])
      : "r"(a[0]), "r"(a[1]), "r"(a[2]), "r"(a[3]), "l"(db));
}

constexpr int K1_XB = 17408;
constexpr int K1_X = 0, K1_W = 8 * K1_XB, K1_STAGE = 24576, K1_NST = 3;
constexpr int K1_PART = K1_W + K1_NST * K1_STAGE, K1_TAB = K1_PART + 3 * 128 * 8, K1_BAR = K1_TAB + 128 * 8, K1_SMEM = K1_BAR + 128;
constexpr float Q_SCALE = 0.25f * 1.4426950408889634f;

#define K1_UNROLL 8
constexpr int kK1Unroll = K1_UNROLL;
#define K1_PF 0
#define K1_MC 0
__global__ void __launch_bounds__(416, 1)
k1_ln_qkv(const __grid_constant__ CUtensorMap tm_x, const __grid_constant__ CUtensorMap tm_wqkv, const uint8_t* __restrict__ x_raw, const uint8_t* __restrict__ w_qkv,
          const uint8_t* __restrict__ w_gate, const uint8_t* __restrict__ w_up, const uint8_t* __restrict__ w_down, const uint8_t* __restrict__ w_o) {
    extern __shared__ __align__(1024) uint8_t smem[];
    const uint32_t sb = smem_u32(smem);
    const uint32_t bar_x = sb + K1_BAR, bar_full = bar_x + 64, bar_empty = bar_full + 8 * K1_NST;
    const int tid = threadIdx.x, lane = tid & 31;
    const int warp = __shfl_sync(~0u, tid >> 5, 0);
    const int rt = blockIdx.x >> 3, ct = blockIdx.x & 7;
    TS_INIT();
    if (tid == 0) GT(0, 0);
    if (tid == 32) { prefetch_map(&tm_x); prefetch_map(&tm_wqkv); }
    if (tid == 0) {
        for (int i = 0; i < 8; i++) mbar_init(bar_x + 8 * i, 1);
        for (int i = 0; i < K1_NST; i++) { mbar_init(bar_full + 8 * i, 1); mbar_init(bar_empty + 8 * i, 12); }
        fence_bar_init();
    }
    if (blockIdx.x == 0 && tid < 32) g_flag[tid] = 0;
    if (tid == 0) for (int kb = 0; kb < 8; kb++) mbar_expect(bar_x + 8 * kb, 16384);
    __syncthreads();
    pdl_launch();
    if (warp == 12) {
        auto load_w = [&](int kb, int st) {
            mbar_expect(bar_full + 8 * st, K1_STAGE);
            for (int b = 0; b < 3; b++) tma_load(sb + K1_W + st * K1_STAGE + b * 8192, &tm_wqkv, ct * 192 + b * 64, kb * 64, bar_full + 8 * st);
        };
        if (elect_one()) {
            for (int kb = 0; kb < 8; kb++) {
                tma_load(sb + K1_X + kb * K1_XB, &tm_x, kb * 64, rt * 128, bar_x + 8 * kb);
                if (kb < K1_NST) load_w(kb, kb);
            }
            for (int kb = K1_NST; kb < 8; kb++) {
                const int st = kb % K1_NST;
                mbar_wait(bar_empty + 8 * st, (kb / K1_NST - 1) & 1);
                load_w(kb, st);
            }
            l2_prefetch(w_gate + blockIdx.x * (D * F * 2 / 128), D * F * 2 / 128);
            l2_prefetch(w_up + blockIdx.x * (D * F * 2 / 128), D * F * 2 / 128);
            l2_prefetch(w_down + blockIdx.x * (D * F * 2 / 128), D * F * 2 / 128);
            l2_prefetch(w_o + blockIdx.x * (D * D * 2 / 128), D * D * 2 / 128);
        }
        return;
    }
    const int wg = warp >> 2, w = warp & 3;
    for (int i = tid; i < 8 * 64; i += 384) {
        const uint32_t v = ((i & 63) < 8) ? 0x3F803F80u : 0u;
        *(uint4*)(smem + K1_X + (i >> 6) * K1_XB + 16384 + (i & 63) * 16) = make_uint4(v, v, v, v);
    }
    fence_async_smem();
    named_bar(1, 384);
    float acc[68];
    const int tok = tid & 127;
    float shift = 0.f, s1[2] = {0.f, 0.f}, s2[2] = {0.f, 0.f};
    {
        uint64_t da = make_desc(sb + K1_W + wg * 8192, 16, 1024, 1), db = make_desc(sb + K1_X, 16, 1024, 1);
        int st = 0, ph = 0, pst = 0;
#pragma unroll kK1Unroll
        for (int kb = 0; kb < 8; kb++) {
            mbar_wait(bar_x + 8 * kb, 0);
            mbar_wait(bar_full + 8 * st, ph);
            WG_FENCE();
#pragma unroll
            for (int k = 0; k < 4; k++) {
                wgmma_n136_ta(acc, da, db, kb | k);
                if (k < 3) DESC_ADV(da, 128); else DESC_ADV(da, st < K1_NST - 1 ? (K1_STAGE >> 4) - 384 : -((K1_NST - 1) * (K1_STAGE >> 4) + 384));
                DESC_ADV(db, k < 3 ? 2 : (K1_XB >> 4) - 6);
            }
            WG_COMMIT();
            if (kb > 0 && kb < 8 - K1_NST + 1) {
                WG_WAIT(1);
                if (lane == 0) mbar_arrive(bar_empty + 8 * pst);
            }
            pst = st;
            if (++st == K1_NST) { st = 0; ph ^= 1; }
            if (kb == 0) shift = bf_lo(*(const uint32_t*)(smem + K1_X + tok * 128 + ((tok & 7) << 4)));
            {
                const uint8_t* row = smem + K1_X + kb * K1_XB + tok * 128;
#pragma unroll
                for (int i = 0; i < 3; i++) {
                    const int c = wg * 3 + i;
                    if (i < 2 || wg < 2) {
                        const uint4 v = *(const uint4*)(row + ((c ^ (tok & 7)) << 4));
                        const uint32_t vv[4] = {v.x, v.y, v.z, v.w};
#pragma unroll
                        for (int e = 0; e < 4; e++) {
                            const float a = bf_lo(vv[e]) - shift, b = bf_hi(vv[e]) - shift;
                            s1[e & 1] += a + b;
                            s2[e & 1] = fmaf(a, a, fmaf(b, b, s2[e & 1]));
                        }
                    }
                }
            }
        }
        if (tid == 0) TS(0, 0);
        *(float2*)(smem + K1_PART + (wg * 128 + tok) * 8) = make_float2(s1[0] + s1[1], s2[0] + s2[1]);
        named_bar(1, 384);
        if (wg == 0) {
            const float2 p0 = *(const float2*)(smem + K1_PART + tok * 8), p1 = *(const float2*)(smem + K1_PART + (128 + tok) * 8),
                         p2 = *(const float2*)(smem + K1_PART + (256 + tok) * 8);
            const float m = (p0.x + p1.x + p2.x) * (1.f / D);
            const float var = fmaxf((p0.y + p1.y + p2.y) * (1.f / D) - m * m, 0.f);
            *(float2*)(smem + K1_TAB + tok * 8) = make_float2(shift + m, rsqrtf(var + 1e-5f));
        }
        named_bar(1, 384);
        {
            for (int r = ct * 16 + warp; r < ct * 16 + 16; r += 12) {
                const float2 st = *(const float2*)(smem + K1_TAB + r * 8);
                const uint8_t* p = smem + K1_X + (lane >> 3) * K1_XB + r * 128 + (((lane & 7) ^ (r & 7)) << 4);
                uint4* g = (uint4*)(g_xn + (size_t)(rt * 128 + r) * D);
#pragma unroll
                for (int hh = 0; hh < 2; hh++) {
                    const uint4 v = *(const uint4*)(p + hh * 4 * K1_XB);
                    uint4 o;
                    o.x = pack2((bf_lo(v.x) - st.x) * st.y, (bf_hi(v.x) - st.x) * st.y);
                    o.y = pack2((bf_lo(v.y) - st.x) * st.y, (bf_hi(v.y) - st.x) * st.y);
                    o.z = pack2((bf_lo(v.z) - st.x) * st.y, (bf_hi(v.z) - st.x) * st.y);
                    o.w = pack2((bf_lo(v.w) - st.x) * st.y, (bf_hi(v.w) - st.x) * st.y);
                    g[hh * 32 + lane] = o;
                }
            }
        }
        WG_WAIT(0);
        keep(acc);
        named_bar(1, 384);
        if (tid == 0) TS(0, 1);
    }
    if (tid == 0) TS(0, 3);
    {
        const int col = ct * 192 + wg * 64 + w * 16;
        const int which = col >> 9, head = (col >> 4) & 31, t = lane & 3;
        const float sc = which == 0 ? Q_SCALE : 1.f;
        const float cs0 = __shfl_sync(~0u, acc[64], lane & ~3), cs1 = __shfl_sync(~0u, acc[66], lane & ~3);
        const uint32_t stg = sb + K1_W + warp * 4096;
#pragma unroll
        for (int jp = 0; jp < 8; jp++) {
            uint32_t r[4];
#pragma unroll
            for (int jj = 0; jj < 2; jj++) {
                const int j = 2 * jp + jj;
                const float4 st = *(const float4*)(smem + K1_TAB + (8 * j + 2 * t) * 8);
                const float a0 = st.y * sc, a1 = st.w * sc;
                r[2 * jj] = pack2(fmaf(-st.x, cs0, acc[4 * j]) * a0, fmaf(-st.z, cs0, acc[4 * j + 1]) * a1);
                r[2 * jj + 1] = pack2(fmaf(-st.x, cs1, acc[4 * j + 2]) * a0, fmaf(-st.z, cs1, acc[4 * j + 3]) * a1);
            }
            const int mi = lane >> 3;
            stsm_x4_t(stg + (mi & 1) * 2048 + (8 * (2 * jp + (mi >> 1)) + (lane & 7)) * 16, r[0], r[1], r[2], r[3]);
        }
        if (tid == 0) TS(0, 4);
        __syncwarp();
        uint4* dst;
        int pitch;
        if (which == 0) { dst = g_q + head * 2 * S + rt * 128; pitch = S; }
        else { dst = g_kv + ((head * 16 + rt) * 4 + (which - 1) * 2) * 128; pitch = 128; }
        const uint4* src = (const uint4*)(smem + K1_W + warp * 4096);
#pragma unroll
        for (int i = 0; i < 8; i++) dst[(i >> 2) * pitch + (i & 3) * 32 + lane] = src[i * 32 + lane];
        if (tid == 0) TS(0, 5);
    }
    if (tid == 0) TS(0, 2);
    if (tid == 0) GT(0, 1);
}

constexpr int K2_WNST = 2;
constexpr int K2_X = 0, K2_W = 131072, K2_XCH = K2_W + K2_WNST * 16384, K2_RING = K2_XCH + 8192, K2_RSTAGE = 10240, K2_RNST = 4;
constexpr int K2_BAR = K2_RING + K2_RNST * K2_RSTAGE, K2_SMEM = K2_BAR + 512;
constexpr int K2_DSTAGE = 24576, K2_DNST = 4;
constexpr int K2_THREADS = 640;
#define FFN_BATCH 4

#define POLY_MASK 0xDADA
#define REFOFF 80.f
constexpr float REF_OFFSET = REFOFF;
constexpr float POLY_LOG2K = -0.052214f;

struct PolyC { uint32_t one, e2; };
__device__ __forceinline__ uint32_t exp2_soft(float a, float b, float bz, const PolyC& c) {
    float ra, rb;
    asm("fma.rn.sat.f32 %0, %1, 0f00000080, %2;" : "=f"(ra) : "f"(a), "f"(bz));
    asm("fma.rn.sat.f32 %0, %1, 0f00000080, %2;" : "=f"(rb) : "f"(b), "f"(bz));
    uint32_t W, G, d, Y;
    asm("cvt.pack.sat.s16.s32 %0, %1, %2;" : "=r"(W) : "r"(__float_as_uint(rb)), "r"(__float_as_uint(ra)));
    asm("lop3.b32 %0, %1, 0x007F007F, %2, 0xEA;" : "=r"(G) : "r"(W), "r"(c.one));
    asm("fma.rn.bf16x2 %0, %1, %2, %3;" : "=r"(d) : "r"(G), "r"(c.e2), "r"(0xBF27BF27u));
    asm("fma.rn.bf16x2 %0, %1, %2, %3;" : "=r"(d) : "r"(G), "r"(d), "r"(0x3EC83EC8u));
    asm("fma.rn.bf16x2 %0, %1, %2, %1;" : "=r"(Y) : "r"(W), "r"(d));
    return Y;
}
__device__ __forceinline__ void softmax_step(const float (&s)[32], uint32_t (&p)[16], float nm0, float nm1, float bz0, float bz1, const PolyC& c) {
#pragma unroll
    for (int i = 0; i < 16; i++)
        if (!((POLY_MASK >> i) & 1)) { const float nm = (i & 1) ? nm1 : nm0; p[i] = pack2(ex2(s[2 * i] + nm), ex2(s[2 * i + 1] + nm)); }
#pragma unroll
    for (int i = 0; i < 16; i++)
        if ((POLY_MASK >> i) & 1) p[i] = exp2_soft(s[2 * i], s[2 * i + 1], (i & 1) ? bz1 : bz0, c);
}
__device__ __forceinline__ void mma16816(float (&d)[4], const uint32_t* a, uint32_t b0, uint32_t b1) {
    asm volatile("mma.sync.aligned.m16n8k16.row.col.f32.bf16.bf16.f32 {%0,%1,%2,%3},{%4,%5,%6,%7},{%8,%9},{%0,%1,%2,%3};"
                 : "+f"(d[0]), "+f"(d[1]), "+f"(d[2]), "+f"(d[3]) : "r"(a[0]), "r"(a[1]), "r"(a[2]), "r"(a[3]), "r"(b0), "r"(b1));
}
__device__ __forceinline__ void attn_rows_true_max(const uint32_t (&qf)[4], const uint4* gkv, __nv_bfloat16* orow, int lane) {
    const int g = lane >> 2, t = lane & 3;
    auto row = [&](int plane, int key) { return gkv + ((key >> 7) * 4 + plane) * 128 + (key & 127); };
    auto kw = [&](int plane, int key) { return ((const uint32_t*)row(plane, key))[t]; };
    auto vw = [&](int plane, int key) { return ((const uint16_t*)row(plane, key))[g] | ((uint32_t)((const uint16_t*)row(plane, key + 1))[g] << 16); };
    float m0 = -INFINITY, m1 = -INFINITY;
#pragma unroll 1
    for (int kb = 0; kb < S / 8; kb++) {
        float s[4] = {0.f, 0.f, 0.f, 0.f};
        mma16816(s, qf, kw(0, kb * 8 + g), kw(1, kb * 8 + g));
        m0 = fmaxf(m0, fmaxf(s[0], s[1]));
        m1 = fmaxf(m1, fmaxf(s[2], s[3]));
    }
    m0 = fmaxf(m0, __shfl_xor_sync(~0u, m0, 1)); m0 = fmaxf(m0, __shfl_xor_sync(~0u, m0, 2));
    m1 = fmaxf(m1, __shfl_xor_sync(~0u, m1, 1)); m1 = fmaxf(m1, __shfl_xor_sync(~0u, m1, 2));
    float o0[4] = {0.f, 0.f, 0.f, 0.f}, o1[4] = {0.f, 0.f, 0.f, 0.f}, l0 = 0.f, l1 = 0.f;
#pragma unroll 1
    for (int kb = 0; kb < S / 16; kb++) {
        float sa[4] = {0.f, 0.f, 0.f, 0.f}, sc[4] = {0.f, 0.f, 0.f, 0.f};
        mma16816(sa, qf, kw(0, kb * 16 + g), kw(1, kb * 16 + g));
        mma16816(sc, qf, kw(0, kb * 16 + 8 + g), kw(1, kb * 16 + 8 + g));
        uint32_t p[4];
        p[0] = pack2(ex2(sa[0] - m0), ex2(sa[1] - m0));
        p[1] = pack2(ex2(sa[2] - m1), ex2(sa[3] - m1));
        p[2] = pack2(ex2(sc[0] - m0), ex2(sc[1] - m0));
        p[3] = pack2(ex2(sc[2] - m1), ex2(sc[3] - m1));
        l0 += bf_lo(p[0]) + bf_hi(p[0]) + bf_lo(p[2]) + bf_hi(p[2]);
        l1 += bf_lo(p[1]) + bf_hi(p[1]) + bf_lo(p[3]) + bf_hi(p[3]);
        const int key = kb * 16 + 2 * t;
        mma16816(o0, p, vw(2, key), vw(2, key + 8));
        mma16816(o1, p, vw(3, key), vw(3, key + 8));
    }
    l0 += __shfl_xor_sync(~0u, l0, 1); l0 += __shfl_xor_sync(~0u, l0, 2);
    l1 += __shfl_xor_sync(~0u, l1, 1); l1 += __shfl_xor_sync(~0u, l1, 2);
    const float i0 = 1.f / l0, i1 = 1.f / l1;
    *(uint32_t*)(orow + 2 * t) = pack2(o0[0] * i0, o0[1] * i0);
    *(uint32_t*)(orow + 8 + 2 * t) = pack2(o1[0] * i0, o1[1] * i0);
    *(uint32_t*)(orow + 8 * D + 2 * t) = pack2(o0[2] * i1, o0[3] * i1);
    *(uint32_t*)(orow + 8 * D + 8 + 2 * t) = pack2(o1[2] * i1, o1[3] * i1);
}

__global__ void __launch_bounds__(K2_THREADS, 1)
k2_attn_ffn(const __grid_constant__ CUtensorMap tm_xn, const __grid_constant__ CUtensorMap tm_wg, const __grid_constant__ CUtensorMap tm_wu,
            const __grid_constant__ CUtensorMap tm_wd, const __grid_constant__ CUtensorMap tm_h, const __grid_constant__ CUtensorMap tm_g, uint32_t zero) {
    extern __shared__ __align__(1024) uint8_t smem[];
    const uint32_t sb = smem_u32(smem);
    const uint32_t bar_rfull = sb + K2_BAR, bar_rempty = bar_rfull + 32;
    const uint32_t bar_x = bar_rempty + 32, bar_wfull = bar_x + 64, bar_dfull = bar_wfull + 8 * K2_WNST;
    const int tid = threadIdx.x, lane = tid & 31;
    const int wg = __shfl_sync(~0u, tid >> 7, 0);
    TS_INIT();
    if (tid == 0) GT(1, 0);
    if (tid == 0) {
        for (int i = 0; i < 4; i++) { mbar_init(bar_rfull + 8 * i, 1); mbar_init(bar_rempty + 8 * i, 16); }
        for (int i = 0; i < K2_WNST; i++) mbar_init(bar_wfull + 8 * i, 1);
        for (int i = 0; i < K2_DNST; i++) mbar_init(bar_dfull + 8 * i, 1);
        for (int i = 0; i < 8; i++) mbar_init(bar_x + 8 * i, 1);
        fence_bar_init();
    }
    if (tid < K2_RNST * 128) *(uint4*)(smem + K2_RING + (tid >> 7) * K2_RSTAGE + 8192 + (tid & 127) * 16) = make_uint4(0x00003F80u, 0, 0, 0);
    fence_async_smem();
    __syncthreads();
    pdl_launch();

    if (wg < 4) {
        pdl_wait();
        if (tid == 0) TS(1, 0);
        if (tid == 0) GT(1, 2);
        const int head = blockIdx.x >> 2, part = blockIdx.x & 3;
        const int warp4 = (tid >> 5) & 3;
        const uint4* gq = g_q + head * 2 * S;
        PolyC pc;
        pc.one = 0x3F803F80u ^ zero;
        pc.e2 = 0x3E623E62u ^ zero;
        const uint64_t dk0 = make_desc(sb + K2_RING, 2048, 128, 0), dv0 = make_desc(sb + K2_RING + 4096, 128, 2048, 0);
        constexpr int RS = K2_RSTAGE >> 4;
        uint32_t qf[4];
        auto load_q = [&](int rnd) {
            const uint32_t* qp = (const uint32_t*)(gq + part * 512 + (rnd * 4 + wg) * 64 + warp4 * 16 + (lane >> 2)) + (lane & 3);
            qf[0] = qp[0]; qf[1] = qp[32]; qf[2] = qp[S * 4]; qf[3] = qp[S * 4 + 32];
        };
        load_q(0);
#pragma unroll 1
        for (int rnd = 0; rnd < 2; rnd++) {
            const int row0 = part * 512 + (rnd * 4 + wg) * 64 + warp4 * 16;
            float s[32], o[12];
            uint32_t p[16];
            mbar_wait(bar_rfull, 0);
            WG_FENCE(); wgmma_qk(s, qf, dk0); WG_COMMIT(); WG_WAIT(0); keep(s);
            if (wg == 0 && rnd == 0) TS(1, 1);
            float m0 = -INFINITY, m1 = -INFINITY;
#pragma unroll
            for (int i = 0; i < 32; i += 4) { m0 = fmaxf(m0, fmaxf(s[i], s[i + 1])); m1 = fmaxf(m1, fmaxf(s[i + 2], s[i + 3])); }
            m0 = fmaxf(m0, __shfl_xor_sync(~0u, m0, 1)); m0 = fmaxf(m0, __shfl_xor_sync(~0u, m0, 2));
            m1 = fmaxf(m1, __shfl_xor_sync(~0u, m1, 1)); m1 = fmaxf(m1, __shfl_xor_sync(~0u, m1, 2));
            m0 = ceilf(m0) + REF_OFFSET; m1 = ceilf(m1) + REF_OFFSET;
            float nm0 = POLY_LOG2K - m0, nm1 = POLY_LOG2K - m1;
            float bz0 = __fmul_rn(__fmul_rn(127.0f - m0, 0x1p-71f), 0x1p-71f), bz1 = __fmul_rn(__fmul_rn(127.0f - m1, 0x1p-71f), 0x1p-71f);
            asm volatile("" : "+f"(nm0), "+f"(nm1), "+f"(bz0), "+f"(bz1));
#pragma unroll
            for (int i = 0; i < 12; i++) o[i] = 0.f;
#pragma unroll 1
            for (int it = 0; it < 8; it++) {
                const int s0 = (it & 1) * 2;
                const uint32_t par = (it >> 1) & 1;
                uint64_t dk = dk0 + s0 * RS, dv = dv0 + s0 * RS;
#pragma unroll
                for (int u = 0; u < 4; u++) {
                    if (u == 0 || u == 2) mbar_wait(bar_rfull + 8 * (s0 + (u >> 1)), par);
                    WG_FENCE(); wgmma_qk(s, qf, dk); WG_COMMIT();
                    if (u == 1) DESC_ADV(dk, 576); else DESC_ADV(dk, 64);
                    WG_WAIT(0); keep(s);
                    if (u == 2 && lane == 0) mbar_arrive(bar_rempty + 8 * s0);
                    if (u == 0 && it > 0 && lane == 0) mbar_arrive(bar_rempty + 8 * ((s0 + 3) & 3));
                    softmax_step(s, p, nm0, nm1, bz0, bz1, pc);
                    WG_FENCE();
                    wgmma_pv(o, p, dv); DESC_ADV(dv, 16);
                    wgmma_pv(o, p + 4, dv); DESC_ADV(dv, 16);
                    wgmma_pv(o, p + 8, dv); DESC_ADV(dv, 16);
                    wgmma_pv(o, p + 12, dv);
                    if (u == 1) DESC_ADV(dv, 528); else DESC_ADV(dv, 16);
                    WG_COMMIT();
                }
            }
            uint32_t qo[4] = {qf[0], qf[1], qf[2], qf[3]};
            if (rnd == 0) load_q(1);
            WG_WAIT(0);
            keep(o);
            if (lane == 0) mbar_arrive(bar_rempty + 8 * 3);
            const float l0 = __shfl_sync(~0u, o[8], lane & ~3), l1 = __shfl_sync(~0u, o[10], lane & ~3);
            bool bad = !(l0 < 0x1p120f) || !(l1 < 0x1p120f);
#pragma unroll
            for (int i = 0; i < 8; i++) bad = bad || !(fabsf(o[i]) < INFINITY);
            __nv_bfloat16* orow = g_o + (size_t)(row0 + (lane >> 2)) * D + head * 16;
            if (__any_sync(~0u, bad)) {
                attn_rows_true_max(qo, g_kv + head * 8192, orow, lane);
            } else {
                const float i0 = rcp(l0), i1 = rcp(l1);
                const int t = lane & 3;
                *(uint32_t*)(orow + 2 * t) = pack2(o[0] * i0, o[1] * i0);
                *(uint32_t*)(orow + 8 + 2 * t) = pack2(o[4] * i0, o[5] * i0);
                *(uint32_t*)(orow + 8 * D + 2 * t) = pack2(o[2] * i1, o[3] * i1);
                *(uint32_t*)(orow + 8 * D + 8 + 2 * t) = pack2(o[6] * i1, o[7] * i1);
            }
            TS(1, 2 + rnd * 4 + wg);
        }
        if (tid == 0) GT(1, 1);
    } else {
        const int rt = blockIdx.x >> 3, ct = blockIdx.x & 7;
        const int w = __shfl_sync(~0u, (tid >> 5) & 3, 0);
        float acc[64];
        const uint4* gkv = g_kv + (blockIdx.x >> 2) * 8192;
        int rn = 0;
        auto ring_issue = [&]() {
            if (elect_one()) {
                mbar_expect(bar_rfull + 8 * (rn & 3), 8192);
                bulk_load(sb + K2_RING + (rn & 3) * K2_RSTAGE, gkv + (rn & 15) * 512, 8192, bar_rfull + 8 * (rn & 3));
            }
            rn++;
        };
        auto ring_ready = [&]() { return mbar_test(bar_rempty + 8 * (rn & 3), ((rn >> 2) & 1) ^ 1); };
        auto ring_poll = [&]() { if (w == 1 && rn < 32 && ring_ready()) ring_issue(); };
        auto ring_drain = [&]() { if (w == 1) while (rn < 32) { mbar_wait(bar_rempty + 8 * (rn & 3), ((rn >> 2) & 1) ^ 1); ring_issue(); } };
        auto load_w = [&](int n, int stage) {
            if (elect_one()) {
                const int col = ct * 224 + (n >> 2) * 32, k = (n & 3) * 128;
                mbar_expect(bar_wfull + 8 * stage, 16384);
                tma_load(sb + K2_W + stage * 16384, &tm_wg, col, k, bar_wfull + 8 * stage);
                tma_load(sb + K2_W + stage * 16384 + 8192, &tm_wu, col, k, bar_wfull + 8 * stage);
            }
        };
        auto released = [&](int id) { if (w == 0) named_bar(id, 128); else named_arrive(id, 128); };
        if (w == 0) { load_w(0, 0); load_w(1, 1); }
        pdl_wait();
        if (w == 1) { ring_issue(); ring_issue(); ring_issue(); ring_issue(); }
        if (w == 0 && elect_one()) {
            for (int kb = 0; kb < 8; kb++) { mbar_expect(bar_x + 8 * kb, 16384); tma_load(sb + K2_X + kb * 16384, &tm_xn, kb * 64, rt * 128, bar_x + 8 * kb); }
        }
        {
            uint64_t da = make_desc(sb + K2_W, 8192, 512, 2), db = make_desc(sb + K2_X, 16, 1024, 1);
            uint32_t mine[16];
            auto finish_tile = [&](int tile) {
                named_bar(2, 128);
                if (tile == 4 && w == 3 && lane == 0) asm volatile("red.release.gpu.global.add.u32 [%0], 1;" ::"l"(&g_flag[rt * 2]) : "memory");
                const uint4* xr = (const uint4*)(smem + K2_XCH) + (w ^ 2) * 128 + lane;
#pragma unroll
                for (int i = 0; i < 4; i++) {
                    const uint4 r = xr[i * 32];
                    const uint32_t rr[4] = {r.x, r.y, r.z, r.w};
#pragma unroll
                    for (int e = 0; e < 4; e++) asm("mul.rn.bf16x2 %0, %0, %1;" : "+r"(mine[4 * i + e]) : "r"(rr[e]));
                }
                const int g = lane >> 2, t = lane & 3, odd = t & 1;
                __nv_bfloat16* hrow = g_h + (size_t)(ct * 224 + tile * 32 + (w & 1) * 16 + g) * S + rt * 128 + (w >> 1) * 64 + odd * 8 + (t >> 1) * 4;
#pragma unroll
                for (int jp = 0; jp < 4; jp++)
#pragma unroll
                    for (int r = 0; r < 2; r++) {
                        const uint32_t a = mine[4 * jp + r], b = mine[4 * jp + 2 + r];
                        const uint32_t got = __shfl_xor_sync(~0u, odd ? a : b, 1);
                        *(uint2*)(hrow + (size_t)r * 8 * S + jp * 16) = odd ? make_uint2(got, b) : make_uint2(a, got);
                    }
            };
#pragma unroll 1
            for (int tile = 0; tile < 7; tile++) {
#pragma unroll
                for (int kd = 0; kd < 4; kd++) {
                    if (tile == 0) { mbar_wait(bar_x + 16 * kd, 0); mbar_wait(bar_x + 16 * kd + 8, 0); }
                    mbar_wait(bar_wfull + 8 * (kd & 1), kd >> 1);
                    WG_FENCE();
#pragma unroll
                    for (int k = 0; k < 8; k++) {
                        wgmma_n128_ta(acc, da, db, kd | k);
                        DESC_ADV(da, k < 7 ? 64 : ((kd & 1) == 0 ? 1024 - 448 : -(1024 + 448)));
                        DESC_ADV(db, (k & 3) < 3 ? 2 : (k == 3 || kd < 3 ? 1024 - 6 : -(7 * 1024 + 6)));
                        if (k == 1 && kd > 0) {
                            WG_COMMIT();
                            WG_WAIT(1);
                            released(3 + (kd & 1));
                            if (w == 0 && (kd < 3 || tile < 6)) load_w(tile * 4 + kd + 1, (kd - 1) & 1);
                            WG_FENCE();
                        }
                    }
                    WG_COMMIT();
                    if (kd == 0 && tile > 0) finish_tile(tile - 1);
                    ring_poll();
                }
                WG_WAIT(0);
                released(3);
                if (w == 0 && tile < 6) load_w(tile * 4 + 5, 1);
                keep(acc);
                uint4* xs = (uint4*)(smem + K2_XCH) + w * 128 + lane;
                if (w < 2) {
#pragma unroll
                    for (int i = 0; i < 16; i++) mine[i] = pack2(acc[2 * i], acc[2 * i + 1]);
#pragma unroll
                    for (int i = 0; i < 4; i++)
                        xs[i * 32] = make_uint4(pack2(acc[32 + 8 * i], acc[33 + 8 * i]), pack2(acc[34 + 8 * i], acc[35 + 8 * i]),
                                                pack2(acc[36 + 8 * i], acc[37 + 8 * i]), pack2(acc[38 + 8 * i], acc[39 + 8 * i]));
                } else {
#pragma unroll
                    for (int i = 0; i < 16; i++) mine[i] = pack2(acc[32 + 2 * i], acc[33 + 2 * i]);
#pragma unroll
                    for (int i = 0; i < 4; i++)
                        xs[i * 32] = make_uint4(pack2(acc[8 * i], acc[1 + 8 * i]), pack2(acc[2 + 8 * i], acc[3 + 8 * i]),
                                                pack2(acc[4 + 8 * i], acc[5 + 8 * i]), pack2(acc[6 + 8 * i], acc[7 + 8 * i]));
                }
            }
            finish_tile(6);
        }
        TS(1, 10);
        named_bar(2, 128);
        if (w == 3 && lane == 0) asm volatile("red.release.gpu.global.add.u32 [%0], 1;" ::"l"(&g_flag[rt * 2 + 1]) : "memory");
        auto wait_flag = [&](int which) {
            if (lane == 0) {
                unsigned v;
                int spin = 0;
                do {
                    asm volatile("ld.acquire.gpu.global.u32 %0, [%1];" : "=r"(v) : "l"(&g_flag[rt * 2 + which]) : "memory");
                    if (v < 8) __nanosleep(64);
                } while (v < 8 && ++spin < (1 << 22));
                if (v < 8) __trap();
            }
            __syncwarp();
            asm volatile("fence.proxy.async.global;" ::: "memory");
        };
        auto load_d = [&](int i, int stage) {
            if (i == 0) wait_flag(0);
            if (i == 12) wait_flag(1);
            if (elect_one()) {
                const int j = (i < 12) ? 7 * (i / 3) + ((0x410 >> (4 * (i % 3))) & 7) : 7 * ((i - 12) >> 2) + ((0x6532 >> (4 * ((i - 12) & 3))) & 7);
                const uint32_t dst = sb + K2_X + stage * K2_DSTAGE;
                mbar_expect(bar_dfull + 8 * stage, K2_DSTAGE);
                tma_load(dst, &tm_wd, ct * 64, j * 64, bar_dfull + 8 * stage);
                tma_load(dst + 8192, &tm_h, rt * 128, j * 64, bar_dfull + 8 * stage);
                tma_load(dst + 16384, &tm_h, rt * 128 + 64, j * 64, bar_dfull + 8 * stage);
            }
        };
        if (w == 0) { load_d(0, 0); load_d(1, 1); load_d(2, 2); load_d(3, 3); }
        {
            uint64_t da = make_desc(sb + K2_X, 16, 1024, 1), db = make_desc(sb + K2_X + 8192, 8192, 1024, 1);
            {
                int spin = 0;
                while (!mbar_test(bar_dfull, 0)) { ring_poll(); if (++spin > (1 << 26)) __trap(); }
            }
            TS(1, 11);
#pragma unroll 1
            for (int it = 0; it < 7; it++) {
#pragma unroll
                for (int q = 0; q < 4; q++) {
                    constexpr int DS = K2_DSTAGE >> 4;
                    mbar_wait(bar_dfull + 8 * q, it & 1);
                    WG_FENCE();
#pragma unroll
                    for (int k = 0; k < 4; k++) {
                        wgmma_n128_tab(acc, da, db, it | q | k);
                        const int adv = k < 3 ? 128 : (q < 3 ? DS - 384 : -(3 * DS + 384));
                        DESC_ADV(da, adv); DESC_ADV(db, adv);
                        if (k == 1 && (q > 0 || it > 0)) {
                            WG_COMMIT();
                            WG_WAIT(1);
                            released(3 + (q & 1));
                            const int n = it * 4 + q + 3;
                            if (w == 0 && n < 28) load_d(n, (q + 3) & 3);
                            WG_FENCE();
                        }
                    }
                    WG_COMMIT();
                    if (q & 1) ring_poll();
                }
            }
            WG_WAIT(0);
            keep(acc);
            TS(1, 12);
#pragma unroll
            for (int i = 0; i < 8; i++) {
                uint32_t gv[4];
#pragma unroll
                for (int e = 0; e < 4; e++) {
                    const float y0 = acc[8 * i + 2 * e], y1 = acc[8 * i + 2 * e + 1];
                    gv[e] = pack2(__fdividef(y0, 1.f + __expf(-y0)), __fdividef(y1, 1.f + __expf(-y1)));
                }
                const int mi = lane >> 3;
                const int tok = 8 * (2 * i + (mi >> 1)) + (lane & 7);
                const int chunk = 2 * w + (mi & 1);
                stsm_x4_t(sb + K2_W + tok * 128 + ((chunk ^ (tok & 7)) << 4), gv[0], gv[1], gv[2], gv[3]);
            }
            fence_async_smem();
            named_bar(2, 128);
            if (w == 0 && elect_one()) {
                tma_store(&tm_g, ct * 64, rt * 128, sb + K2_W);
                asm volatile("cp.async.bulk.wait_group.read 0;" ::: "memory");
            }
            TS(1, 13);
            if (tid == 512) GT(1, 3);
        }
        ring_drain();
    }
}

constexpr int K3_A = 0, K3_B = 65536, K3_BAR = K3_B + 131072, K3_SMEM = K3_BAR + 128;

__global__ void __launch_bounds__(256, 1)
k3_out(const __grid_constant__ CUtensorMap tm_o, const __grid_constant__ CUtensorMap tm_wo, const __nv_bfloat16* __restrict__ x, __nv_bfloat16* __restrict__ out) {
    extern __shared__ __align__(1024) uint8_t smem[];
    const uint32_t sb = smem_u32(smem);
    const uint32_t bar_a = sb + K3_BAR, bar_b = bar_a + 64;
    const int tid = threadIdx.x, lane = tid & 31;
    const int warp = __shfl_sync(~0u, tid >> 5, 0);
    const int rt = blockIdx.x >> 2, ct = blockIdx.x & 3;
    TS_INIT();
    if (tid == 0) GT(2, 0);
    if (warp == 0 && elect_one()) {
        for (int i = 0; i < 8; i++) mbar_init(bar_a + 8 * i, 1);
        mbar_init(bar_b, 1);
        fence_bar_init();
        mbar_expect(bar_b, 131072);
        for (int kb = 0; kb < 8; kb++)
            for (int hh = 0; hh < 2; hh++) tma_load(sb + K3_B + hh * 65536 + kb * 8192, &tm_wo, ct * 128 + hh * 64, kb * 64, bar_b);
    }
    const int wg = warp >> 2, g = lane >> 2, t = lane & 3;
    const size_t e0 = (size_t)(rt * 64 + (warp & 3) * 16 + g) * D + ct * 128 + wg * 64 + 2 * t;
    uint32_t xv[16], gv[16];
#pragma unroll
    for (int j = 0; j < 8; j++) { xv[2 * j] = *(const uint32_t*)(x + e0 + 8 * j); xv[2 * j + 1] = *(const uint32_t*)(x + e0 + 8 * D + 8 * j); }
    __syncthreads();
    pdl_wait();
    if (tid == 0) TS(2, 0);
    if (tid == 0) GT(2, 2);
    if (warp == 0 && elect_one()) {
        for (int kb = 0; kb < 8; kb++) { mbar_expect(bar_a + 8 * kb, 8192); tma_load(sb + K3_A + kb * 8192, &tm_o, kb * 64, rt * 64, bar_a + 8 * kb); }
    }
#pragma unroll
    for (int j = 0; j < 8; j++) { gv[2 * j] = *(const uint32_t*)(g_g + e0 + 8 * j); gv[2 * j + 1] = *(const uint32_t*)(g_g + e0 + 8 * D + 8 * j); }
    float acc[32];
    uint64_t da = make_desc(sb + K3_A, 16, 1024, 1), db = make_desc(sb + K3_B + wg * 65536, 16, 1024, 1);
    mbar_wait(bar_b, 0);
#pragma unroll
    for (int kb = 0; kb < 8; kb++) {
        mbar_wait(bar_a + 8 * kb, 0);
        WG_FENCE();
#pragma unroll
        for (int k = 0; k < 4; k++) {
            wgmma_n64_tb(acc, da, db, kb | k);
            DESC_ADV(da, k < 3 ? 2 : 512 - 6);
            DESC_ADV(db, 128);
        }
        WG_COMMIT();
    }
    WG_WAIT(0);
    keep(acc);
    if (tid == 0) TS(2, 1);
#pragma unroll
    for (int j = 0; j < 8; j++) {
        *(uint32_t*)(out + e0 + 8 * j) = pack2(fmaf(acc[4 * j], bf_lo(gv[2 * j]), bf_lo(xv[2 * j])), fmaf(acc[4 * j + 1], bf_hi(gv[2 * j]), bf_hi(xv[2 * j])));
        *(uint32_t*)(out + e0 + 8 * D + 8 * j) =
            pack2(fmaf(acc[4 * j + 2], bf_lo(gv[2 * j + 1]), bf_lo(xv[2 * j + 1])), fmaf(acc[4 * j + 3], bf_hi(gv[2 * j + 1]), bf_hi(xv[2 * j + 1])));
    }
    if (tid == 0) GT(2, 1);
}

typedef CUresult (*EncodeFn)(CUtensorMap*, CUtensorMapDataType, cuuint32_t, void*, const cuuint64_t*, const cuuint64_t*, const cuuint32_t*,
                             const cuuint32_t*, CUtensorMapInterleave, CUtensorMapSwizzle, CUtensorMapL2promotion, CUtensorMapFloatOOBfill);

CUtensorMap make_map(EncodeFn fn, const void* ptr, int rows, int cols, int box_rows, int box_cols, CUtensorMapSwizzle swz) {
    CUtensorMap m;
    const cuuint64_t dims[2] = {(cuuint64_t)cols, (cuuint64_t)rows};
    const cuuint64_t strides[1] = {(cuuint64_t)cols * 2};
    const cuuint32_t box[2] = {(cuuint32_t)box_cols, (cuuint32_t)box_rows};
    const cuuint32_t estr[2] = {1, 1};
    fn(&m, CU_TENSOR_MAP_DATA_TYPE_BFLOAT16, 2, const_cast<void*>(ptr), dims, strides, box, estr, CU_TENSOR_MAP_INTERLEAVE_NONE, swz,
       CU_TENSOR_MAP_L2_PROMOTION_L2_256B, CU_TENSOR_MAP_FLOAT_OOB_FILL_NONE);
    return m;
}

template <typename... KArgs, typename... Args>
void launch(void (*kern)(KArgs...), int grid, int block, int smem, bool pdl, Args... args) {
    cudaLaunchConfig_t cfg = {};
    cfg.gridDim = dim3(grid);
    cfg.blockDim = dim3(block);
    cfg.dynamicSmemBytes = smem;
    cfg.stream = cudaStreamPerThread;
    cudaLaunchAttribute at[1];
    at[0].id = cudaLaunchAttributeProgrammaticStreamSerialization;
    at[0].val.programmaticStreamSerializationAllowed = 1;
    cfg.attrs = at;
    cfg.numAttrs = pdl ? 1 : 0;
    cudaLaunchKernelEx(&cfg, kern, KArgs(args)...);
}

}

extern "C" void kernel_launch(void* const* d_in, const int* in_sizes, int n_in, void* d_out, int out_size) {
    (void)in_sizes; (void)n_in; (void)out_size;
    const __nv_bfloat16* x = (const __nv_bfloat16*)d_in[0];
    const void* wqkv = d_in[1];
    const void* wo = d_in[2];
    const void* wgate = d_in[4];
    const void* wup = d_in[5];
    const void* wdown = d_in[6];

    static EncodeFn encode = nullptr;
    static void *p_xn, *p_h, *p_o, *p_g;
    if (!encode) {
        void* fn = nullptr;
        cudaDriverEntryPointQueryResult qr;
        cudaGetDriverEntryPoint("cuTensorMapEncodeTiled", &fn, cudaEnableDefault, &qr);
        encode = (EncodeFn)fn;
        cudaGetSymbolAddress(&p_xn, g_xn);
        cudaGetSymbolAddress(&p_h, g_h);
        cudaGetSymbolAddress(&p_o, g_o);
        cudaGetSymbolAddress(&p_g, g_g);
        cudaFuncSetAttribute(k1_ln_qkv, cudaFuncAttributeMaxDynamicSharedMemorySize, K1_SMEM);
        cudaFuncSetAttribute(k2_attn_ffn, cudaFuncAttributeMaxDynamicSharedMemorySize, K2_SMEM);
        cudaFuncSetAttribute(k3_out, cudaFuncAttributeMaxDynamicSharedMemorySize, K3_SMEM);
    }
    const CUtensorMapSwizzle S128 = CU_TENSOR_MAP_SWIZZLE_128B, S64 = CU_TENSOR_MAP_SWIZZLE_64B;
    const CUtensorMap tm_x = make_map(encode, x, S, D, 128, 64, S128);
    const CUtensorMap tm_wqkv = make_map(encode, wqkv, D, 3 * D, 64, 64, S128);
    const CUtensorMap tm_xn = make_map(encode, p_xn, S, D, 128, 64, S128);
    const CUtensorMap tm_wg = make_map(encode, wgate, D, F, 128, 32, S64);
    const CUtensorMap tm_wu = make_map(encode, wup, D, F, 128, 32, S64);
    const CUtensorMap tm_wd = make_map(encode, wdown, F, D, 64, 64, S128);
    const CUtensorMap tm_h = make_map(encode, p_h, F, S, 64, 64, S128);
    const CUtensorMap tm_g = make_map(encode, p_g, S, D, 128, 64, S128);
    const CUtensorMap tm_o = make_map(encode, p_o, S, D, 64, 64, S128);
    const CUtensorMap tm_wo = make_map(encode, wo, D, D, 64, 64, S128);

    launch(k1_ln_qkv, 128, 416, K1_SMEM, false, tm_x, tm_wqkv, (const uint8_t*)x, (const uint8_t*)wqkv, (const uint8_t*)wgate, (const uint8_t*)wup, (const uint8_t*)wdown, (const uint8_t*)wo);
    launch(k2_attn_ffn, 128, K2_THREADS, K2_SMEM, true, tm_xn, tm_wg, tm_wu, tm_wd, tm_h, tm_g, 0u);
    launch(k3_out, 128, 256, K3_SMEM, true, tm_o, tm_wo, x, (__nv_bfloat16*)d_out);
}
```

```cpp
#include <cuda_runtime.h>
#include <cuda_bf16.h>
#include <cuda.h>
#include <stdint.h>

namespace {

constexpr int S = 2048, D = 512, H = 32, F = 1792;

__device__ __align__(1024) uint4 g_q[H * 2 * S];
__device__ __align__(1024) uint4 g_kv[H * 16 * 4 * 128];
__device__ __align__(1024) __nv_bfloat16 g_xn[S * D];
__device__ __align__(1024) __nv_bfloat16 g_h[F * S];
__device__ __align__(1024) __nv_bfloat16 g_o[S * D];
constexpr int FLAG_H = 0, FLAG_O = 32, FLAG_N = 160;
__device__ unsigned g_flag[FLAG_N];
#define TS(k, i)
#define GT(k, i)
#define TS_INIT()

__device__ __forceinline__ uint32_t smem_u32(const void* p) { return (uint32_t)__cvta_generic_to_shared(p); }
__device__ __forceinline__ void mbar_init(uint32_t b, uint32_t n) { asm volatile("mbarrier.init.shared::cta.b64 [%0], %1;" ::"r"(b), "r"(n)); }
__device__ __forceinline__ void mbar_expect(uint32_t b, uint32_t bytes) { asm volatile("mbarrier.arrive.expect_tx.shared::cta.b64 _, [%0], %1;" ::"r"(b), "r"(bytes) : "memory"); }
__device__ __forceinline__ void mbar_arrive(uint32_t b) { asm volatile("mbarrier.arrive.shared::cta.b64 _, [%0];" ::"r"(b) : "memory"); }
__device__ __forceinline__ void mbar_wait(uint32_t b, uint32_t parity) {
    asm volatile("{\n .reg .pred p;\n .reg .u32 c;\n"
                 " mbarrier.try_wait.parity.shared::cta.b64 p, [%0], %1;\n @p bra LAB_DONE;\n mov.u32 c, 0;\n"
                 "LAB_WAIT:\n mbarrier.try_wait.parity.shared::cta.b64 p, [%0], %1;\n @p bra LAB_DONE;\n"
                 " add.u32 c, c, 1;\n setp.lt.u32 p, c, 0x1000000;\n @p bra LAB_WAIT;\n trap;\n"
                 "LAB_DONE:\n}" ::"r"(b), "r"(parity) : "memory");
}
__device__ __forceinline__ bool mbar_test(uint32_t b, uint32_t parity) {
    uint32_t ok;
    asm volatile("{ .reg .pred p; mbarrier.test_wait.parity.shared::cta.b64 p, [%1], %2; selp.b32 %0, 1, 0, p; }" : "=r"(ok) : "r"(b), "r"(parity) : "memory");
    return ok;
}
__device__ __forceinline__ bool elect_one() {
    uint32_t p;
    asm volatile("{ .reg .pred p; elect.sync _|p, 0xffffffff; selp.b32 %0, 1, 0, p; }" : "=r"(p));
    return p;
}
__device__ __forceinline__ void flag_publish(int i) { asm volatile("red.release.gpu.global.add.u32 [%0], 1;" ::"l"(&g_flag[i]) : "memory"); }
__device__ __forceinline__ void flag_wait(int i, unsigned target) {
    unsigned v;
    int spin = 0;
    for (;;) {
        asm volatile("ld.acquire.gpu.global.u32 %0, [%1];" : "=r"(v) : "l"(&g_flag[i]) : "memory");
        if (v >= target) break;
        if (++spin > (1 << 22)) __trap();
        __nanosleep(32);
    }
}
__device__ __forceinline__ void fence_async_smem() { asm volatile("fence.proxy.async.shared::cta;" ::: "memory"); }
__device__ __forceinline__ void fence_bar_init() { asm volatile("fence.mbarrier_init.release.cluster;" ::: "memory"); }
__device__ __forceinline__ void named_bar(int id, int n) { asm volatile("bar.sync %0, %1;" ::"r"(id), "r"(n) : "memory"); }
__device__ __forceinline__ void named_arrive(int id, int n) { asm volatile("bar.arrive %0, %1;" ::"r"(id), "r"(n) : "memory"); }
__device__ __forceinline__ void pdl_wait() { asm volatile("griddepcontrol.wait;" ::: "memory"); }
__device__ __forceinline__ void pdl_launch() { asm volatile("griddepcontrol.launch_dependents;" ::: "memory"); }
__device__ __forceinline__ void tma_load(uint32_t dst, const CUtensorMap* m, int c0, int c1, uint32_t bar) {
    asm volatile("cp.async.bulk.tensor.2d.shared::cluster.global.mbarrier::complete_tx::bytes [%0], [%1, {%3, %4}], [%2];"
                 ::"r"(dst), "l"(m), "r"(bar), "r"(c0), "r"(c1) : "memory");
}
__device__ __forceinline__ void tma_store(const CUtensorMap* m, int c0, int c1, uint32_t src) {
    asm volatile("cp.async.bulk.tensor.2d.global.shared::cta.bulk_group [%0, {%2, %3}], [%1];" ::"l"(m), "r"(src), "r"(c0), "r"(c1) : "memory");
    asm volatile("cp.async.bulk.commit_group;" ::: "memory");
}
__device__ __forceinline__ void tma_load_mc(uint32_t dst, const CUtensorMap* m, int c0, int c1, uint32_t bar, uint16_t mask) {
    asm volatile("cp.async.bulk.tensor.2d.shared::cluster.global.mbarrier::complete_tx::bytes.multicast::cluster [%0], [%1, {%3, %4}], [%2], %5;"
                 ::"r"(dst), "l"(m), "r"(bar), "r"(c0), "r"(c1), "h"(mask) : "memory");
}
__device__ __forceinline__ void cluster_sync() { asm volatile("barrier.cluster.arrive.release.aligned;\n barrier.cluster.wait.acquire.aligned;" ::: "memory"); }
__device__ __forceinline__ void bulk_load(uint32_t dst, const void* src, uint32_t bytes, uint32_t bar) {
    asm volatile("cp.async.bulk.shared::cluster.global.mbarrier::complete_tx::bytes [%0], [%1], %2, [%3];" ::"r"(dst), "l"(src), "r"(bytes), "r"(bar) : "memory");
}
__device__ __forceinline__ void prefetch_map(const CUtensorMap* m) { asm volatile("prefetch.tensormap [%0];" ::"l"(m) : "memory"); }
__device__ __forceinline__ void l2_prefetch(const void* p, uint32_t bytes) { asm volatile("cp.async.bulk.prefetch.L2.global [%0], %1;" ::"l"(p), "r"(bytes) : "memory"); }
__device__ __forceinline__ void stsm_x4_t(uint32_t a, uint32_t r0, uint32_t r1, uint32_t r2, uint32_t r3) {
    asm volatile("stmatrix.sync.aligned.m8n8.x4.trans.shared.b16 [%0], {%1,%2,%3,%4};" ::"r"(a), "r"(r0), "r"(r1), "r"(r2), "r"(r3) : "memory");
}
#define WG_FENCE() asm volatile("wgmma.fence.sync.aligned;" ::: "memory")
#define WG_COMMIT() asm volatile("wgmma.commit_group.sync.aligned;" ::: "memory")
#define WG_WAIT(n) asm volatile("wgmma.wait_group.sync.aligned " #n ";" ::: "memory")
#define DESC_ADV(d, n) asm volatile("add.s64 %0, %0, %1;" : "+l"(d) : "l"((long long)(n)))
template <int N> __device__ __forceinline__ void keep(float (&a)[N]) {
#pragma unroll
    for (int i = 0; i < N; i++) asm volatile("" : "+f"(a[i])::"memory");
}
__device__ __forceinline__ uint64_t make_desc(uint32_t addr, uint32_t lbo, uint32_t sbo, uint32_t swz) {
    return (uint64_t)((addr & 0x3FFFF) >> 4) | ((uint64_t)(lbo >> 4) << 16) | ((uint64_t)(sbo >> 4) << 32) | ((uint64_t)swz << 62);
}
__device__ __forceinline__ float ex2(float x) { float y; asm("ex2.approx.ftz.f32 %0, %1;" : "=f"(y) : "f"(x)); return y; }
__device__ __forceinline__ float rcp(float x) { float y; asm("rcp.approx.ftz.f32 %0, %1;" : "=f"(y) : "f"(x)); return y; }
__device__ __forceinline__ uint32_t pack2(float lo, float hi) { uint32_t r; asm("cvt.rn.bf16x2.f32 %0, %1, %2;" : "=r"(r) : "f"(hi), "f"(lo)); return r; }
__device__ __forceinline__ float bf_lo(uint32_t v) { return __uint_as_float(v << 16); }
__device__ __forceinline__ float bf_hi(uint32_t v) { return __uint_as_float(v & 0xFFFF0000u); }

__device__ __forceinline__ void wgmma_n136_ta(float (&d)[68], uint64_t da, uint64_t db, int acc) {
    asm volatile("{ .reg .pred p; setp.ne.b32 p, %70, 0;\n"
      "wgmma.mma_async.sync.aligned.m64n136k16.f32.bf16.bf16 {%0,%1,%2,%3,%4,%5,%6,%7,%8,%9,%10,%11,%12,%13,%14,%15,%16,%17,%18,%19,%20,%21,%22,%23,%24,%25,%26,%27,%28,%29,%30,%31,%32,%33,%34,%35,%36,%37,%38,%39,%40,%41,%42,%43,%44,%45,%46,%47,%48,%49,%50,%51,%52,%53,%54,%55,%56,%57,%58,%59,%60,%61,%62,%63,%64,%65,%66,%67}, %68, %69, p, 1, 1, 1, 0; }"
      : "+f"(d[0]),"+f"(d[1]),"+f"(d[2]),"+f"(d[3]),"+f"(d[4]),"+f"(d[5]),"+f"(d[6]),"+f"(d[7]),"+f"(d[8]),"+f"(d[9]),"+f"(d[10]),"+f"(d[11]),"+f"(d[12]),"+f"(d[13]),"+f"(d[14]),"+f"(d[15]),"+f"(d[16]),"+f"(d[17]),"+f"(d[18]),"+f"(d[19]),"+f"(d[20]),"+f"(d[21]),"+f"(d[22]),"+f"(d[23]),"+f"(d[24]),"+f"(d[25]),"+f"(d[26]),"+f"(d[27]),"+f"(d[28]),"+f"(d[29]),"+f"(d[30]),"+f"(d[31]),"+f"(d[32]),"+f"(d[33]),"+f"(d[34]),"+f"(d[35]),"+f"(d[36]),"+f"(d[37]),"+f"(d[38]),"+f"(d[39]),"+f"(d[40]),"+f"(d[41]),"+f"(d[42]),"+f"(d[43]),"+f"(d[44]),"+f"(d[45]),"+f"(d[46]),"+f"(d[47]),"+f"(d[48]),"+f"(d[49]),"+f"(d[50]),"+f"(d[51]),"+f"(d[52]),"+f"(d[53]),"+f"(d[54]),"+f"(d[55]),"+f"(d[56]),"+f"(d[57]),"+f"(d[58]),"+f"(d[59]),"+f"(d[60]),"+f"(d[61]),"+f"(d[62]),"+f"(d[63]),"+f"(d[64]),"+f"(d[65]),"+f"(d[66]),"+f"(d[67])
      : "l"(da), "l"(db), "r"(acc));
}
__device__ __forceinline__ void wgmma_n128_ta(float (&d)[64], uint64_t da, uint64_t db, int acc) {
    asm volatile("{ .reg .pred p; setp.ne.b32 p, %66, 0;\n"
      "wgmma.mma_async.sync.aligned.m64n128k16.f32.bf16.bf16 {%0,%1,%2,%3,%4,%5,%6,%7,%8,%9,%10,%11,%12,%13,%14,%15,%16,%17,%18,%19,%20,%21,%22,%23,%24,%25,%26,%27,%28,%29,%30,%31,%32,%33,%34,%35,%36,%37,%38,%39,%40,%41,%42,%43,%44,%45,%46,%47,%48,%49,%50,%51,%52,%53,%54,%55,%56,%57,%58,%59,%60,%61,%62,%63}, %64, %65, p, 1, 1, 1, 0; }"
      : "+f"(d[0]),"+f"(d[1]),"+f"(d[2]),"+f"(d[3]),"+f"(d[4]),"+f"(d[5]),"+f"(d[6]),"+f"(d[7]),"+f"(d[8]),"+f"(d[9]),"+f"(d[10]),"+f"(d[11]),"+f"(d[12]),"+f"(d[13]),"+f"(d[14]),"+f"(d[15]),"+f"(d[16]),"+f"(d[17]),"+f"(d[18]),"+f"(d[19]),"+f"(d[20]),"+f"(d[21]),"+f"(d[22]),"+f"(d[23]),"+f"(d[24]),"+f"(d[25]),"+f"(d[26]),"+f"(d[27]),"+f"(d[28]),"+f"(d[29]),"+f"(d[30]),"+f"(d[31]),"+f"(d[32]),"+f"(d[33]),"+f"(d[34]),"+f"(d[35]),"+f"(d[36]),"+f"(d[37]),"+f"(d[38]),"+f"(d[39]),"+f"(d[40]),"+f"(d[41]),"+f"(d[42]),"+f"(d[43]),"+f"(d[44]),"+f"(d[45]),"+f"(d[46]),"+f"(d[47]),"+f"(d[48]),"+f"(d[49]),"+f"(d[50]),"+f"(d[51]),"+f"(d[52]),"+f"(d[53]),"+f"(d[54]),"+f"(d[55]),"+f"(d[56]),"+f"(d[57]),"+f"(d[58]),"+f"(d[59]),"+f"(d[60]),"+f"(d[61]),"+f"(d[62]),"+f"(d[63])
      : "l"(da), "l"(db), "r"(acc));
}
__device__ __forceinline__ void wgmma_n128_tab(float (&d)[64], uint64_t da, uint64_t db, int acc) {
    asm volatile("{ .reg .pred p; setp.ne.b32 p, %66, 0;\n"
      "wgmma.mma_async.sync.aligned.m64n128k16.f32.bf16.bf16 {%0,%1,%2,%3,%4,%5,%6,%7,%8,%9,%10,%11,%12,%13,%14,%15,%16,%17,%18,%19,%20,%21,%22,%23,%24,%25,%26,%27,%28,%29,%30,%31,%32,%33,%34,%35,%36,%37,%38,%39,%40,%41,%42,%43,%44,%45,%46,%47,%48,%49,%50,%51,%52,%53,%54,%55,%56,%57,%58,%59,%60,%61,%62,%63}, %64, %65, p, 1, 1, 1, 1; }"
      : "+f"(d[0]),"+f"(d[1]),"+f"(d[2]),"+f"(d[3]),"+f"(d[4]),"+f"(d[5]),"+f"(d[6]),"+f"(d[7]),"+f"(d[8]),"+f"(d[9]),"+f"(d[10]),"+f"(d[11]),"+f"(d[12]),"+f"(d[13]),"+f"(d[14]),"+f"(d[15]),"+f"(d[16]),"+f"(d[17]),"+f"(d[18]),"+f"(d[19]),"+f"(d[20]),"+f"(d[21]),"+f"(d[22]),"+f"(d[23]),"+f"(d[24]),"+f"(d[25]),"+f"(d[26]),"+f"(d[27]),"+f"(d[28]),"+f"(d[29]),"+f"(d[30]),"+f"(d[31]),"+f"(d[32]),"+f"(d[33]),"+f"(d[34]),"+f"(d[35]),"+f"(d[36]),"+f"(d[37]),"+f"(d[38]),"+f"(d[39]),"+f"(d[40]),"+f"(d[41]),"+f"(d[42]),"+f"(d[43]),"+f"(d[44]),"+f"(d[45]),"+f"(d[46]),"+f"(d[47]),"+f"(d[48]),"+f"(d[49]),"+f"(d[50]),"+f"(d[51]),"+f"(d[52]),"+f"(d[53]),"+f"(d[54]),"+f"(d[55]),"+f"(d[56]),"+f"(d[57]),"+f"(d[58]),"+f"(d[59]),"+f"(d[60]),"+f"(d[61]),"+f"(d[62]),"+f"(d[63])
      : "l"(da), "l"(db), "r"(acc));
}
__device__ __forceinline__ void wgmma_n64_tb(float (&d)[32], uint64_t da, uint64_t db, int acc) {
    asm volatile("{ .reg .pred p; setp.ne.b32 p, %34, 0;\n"
      "wgmma.mma_async.sync.aligned.m64n64k16.f32.bf16.bf16 {%0,%1,%2,%3,%4,%5,%6,%7,%8,%9,%10,%11,%12,%13,%14,%15,%16,%17,%18,%19,%20,%21,%22,%23,%24,%25,%26,%27,%28,%29,%30,%31}, %32, %33, p, 1, 1, 0, 1; }"
      : "+f"(d[0]),"+f"(d[1]),"+f"(d[2]),"+f"(d[3]),"+f"(d[4]),"+f"(d[5]),"+f"(d[6]),"+f"(d[7]),"+f"(d[8]),"+f"(d[9]),"+f"(d[10]),"+f"(d[11]),"+f"(d[12]),"+f"(d[13]),"+f"(d[14]),"+f"(d[15]),"+f"(d[16]),"+f"(d[17]),"+f"(d[18]),"+f"(d[19]),"+f"(d[20]),"+f"(d[21]),"+f"(d[22]),"+f"(d[23]),"+f"(d[24]),"+f"(d[25]),"+f"(d[26]),"+f"(d[27]),"+f"(d[28]),"+f"(d[29]),"+f"(d[30]),"+f"(d[31])
      : "l"(da), "l"(db), "r"(acc));
}
__device__ __forceinline__ void wgmma_qk(float (&d)[32], const uint32_t* a, uint64_t db) {
    asm volatile("wgmma.mma_async.sync.aligned.m64n64k16.f32.bf16.bf16 {%0,%1,%2,%3,%4,%5,%6,%7,%8,%9,%10,%11,%12,%13,%14,%15,%16,%17,%18,%19,%20,%21,%22,%23,%24,%25,%26,%27,%28,%29,%30,%31}, {%32,%33,%34,%35}, %36, 0, 1, 1, 0;"
      : "=f"(d[0]),"=f"(d[1]),"=f"(d[2]),"=f"(d[3]),"=f"(d[4]),"=f"(d[5]),"=f"(d[6]),"=f"(d[7]),"=f"(d[8]),"=f"(d[9]),"=f"(d[10]),"=f"(d[11]),"=f"(d[12]),"=f"(d[13]),"=f"(d[14]),"=f"(d[15]),"=f"(d[16]),"=f"(d[17]),"=f"(d[18]),"=f"(d[19]),"=f"(d[20]),"=f"(d[21]),"=f"(d[22]),"=f"(d[23]),"=f"(d[24]),"=f"(d[25]),"=f"(d[26]),"=f"(d[27]),"=f"(d[28]),"=f"(d[29]),"=f"(d[30]),"=f"(d[31])
      : "r"(a[0]), "r"(a[1]), "r"(a[2]), "r"(a[3]), "l"(db));
}
__device__ __forceinline__ void wgmma_qk32(float (&d)[16], const uint32_t* a, uint64_t db) {
    asm volatile("wgmma.mma_async.sync.aligned.m64n32k16.f32.bf16.bf16 {%0,%1,%2,%3,%4,%5,%6,%7,%8,%9,%10,%11,%12,%13,%14,%15}, {%16,%17,%18,%19}, %20, 0, 1, 1, 0;"
      : "=f"(d[0]),"=f"(d[1]),"=f"(d[2]),"=f"(d[3]),"=f"(d[4]),"=f"(d[5]),"=f"(d[6]),"=f"(d[7]),"=f"(d[8]),"=f"(d[9]),"=f"(d[10]),"=f"(d[11]),"=f"(d[12]),"=f"(d[13]),"=f"(d[14]),"=f"(d[15])
      : "r"(a[0]), "r"(a[1]), "r"(a[2]), "r"(a[3]), "l"(db));
}
__device__ __forceinline__ void wgmma_pv(float (&d)[12], const uint32_t* a, uint64_t db) {
    asm volatile("wgmma.mma_async.sync.aligned.m64n24k16.f32.bf16.bf16 {%0,%1,%2,%3,%4,%5,%6,%7,%8,%9,%10,%11}, {%12,%13,%14,%15}, %16, 1, 1, 1, 1;"
      : "+f"(d[0]),"+f"(d[1]),"+f"(d[2]),"+f"(d[3]),"+f"(d[4]),"+f"(d[5]),"+f"(d[6]),"+f"(d[7]),"+f"(d[8]),"+f"(d[9]),"+f"(d[10]),"+f"(d[11])
      : "r"(a[0]), "r"(a[1]), "r"(a[2]), "r"(a[3]), "l"(db));
}

constexpr int K1_XB = 17408;
constexpr int K1_X = 0, K1_W = 8 * K1_XB, K1_STAGE = 24576, K1_NST = 3;
constexpr int K1_PART = K1_W + K1_NST * K1_STAGE, K1_TAB = K1_PART + 3 * 128 * 8, K1_BAR = K1_TAB + 128 * 8, K1_SMEM = K1_BAR + 128;
constexpr float Q_SCALE = 0.25f * 1.4426950408889634f;

#define K1_UNROLL 8
constexpr int kK1Unroll = K1_UNROLL;
#define K1_PF 0
#define K1_MC 0
__global__ void __launch_bounds__(416, 1)
k1_ln_qkv(const __grid_constant__ CUtensorMap tm_x, const __grid_constant__ CUtensorMap tm_wqkv, const uint8_t* __restrict__ x_raw, const uint8_t* __restrict__ w_qkv,
          const uint8_t* __restrict__ w_gate, const uint8_t* __restrict__ w_up, const uint8_t* __restrict__ w_down, const uint8_t* __restrict__ w_o) {
    extern __shared__ __align__(1024) uint8_t smem[];
    const uint32_t sb = smem_u32(smem);
    const uint32_t bar_x = sb + K1_BAR, bar_full = bar_x + 64, bar_empty = bar_full + 8 * K1_NST;
    const int tid = threadIdx.x, lane = tid & 31;
    const int warp = __shfl_sync(~0u, tid >> 5, 0);
    const int rt = blockIdx.x >> 3, ct = blockIdx.x & 7;
    TS_INIT();
    if (tid == 0) GT(0, 0);
    if (tid == 32) { prefetch_map(&tm_x); prefetch_map(&tm_wqkv); }
    if (tid == 0) {
        for (int i = 0; i < 8; i++) mbar_init(bar_x + 8 * i, 1);
        for (int i = 0; i < K1_NST; i++) { mbar_init(bar_full + 8 * i, 1); mbar_init(bar_empty + 8 * i, 12); }
        fence_bar_init();
    }
    if (blockIdx.x == 0 && tid < FLAG_N) g_flag[tid] = 0;
    if (tid == 0) for (int kb = 0; kb < 8; kb++) mbar_expect(bar_x + 8 * kb, 16384);
    __syncthreads();
    pdl_launch();
    if (warp == 12) {
        auto load_w = [&](int kb, int st) {
            mbar_expect(bar_full + 8 * st, K1_STAGE);
            for (int b = 0; b < 3; b++) tma_load(sb + K1_W + st * K1_STAGE + b * 8192, &tm_wqkv, ct * 192 + b * 64, kb * 64, bar_full + 8 * st);
        };
        if (elect_one()) {
            for (int kb = 0; kb < 8; kb++) {
                tma_load(sb + K1_X + kb * K1_XB, &tm_x, kb * 64, rt * 128, bar_x + 8 * kb);
                if (kb < K1_NST) load_w(kb, kb);
            }
            for (int kb = K1_NST; kb < 8; kb++) {
                const int st = kb % K1_NST;
                mbar_wait(bar_empty + 8 * st, (kb / K1_NST - 1) & 1);
                load_w(kb, st);
            }
            l2_prefetch(w_gate + blockIdx.x * (D * F * 2 / 128), D * F * 2 / 128);
            l2_prefetch(w_up + blockIdx.x * (D * F * 2 / 128), D * F * 2 / 128);
            l2_prefetch(w_down + blockIdx.x * (D * F * 2 / 128), D * F * 2 / 128);
            l2_prefetch(w_o + blockIdx.x * (D * D * 2 / 128), D * D * 2 / 128);
        }
        return;
    }
    const int wg = warp >> 2, w = warp & 3;
    for (int i = tid; i < 8 * 64; i += 384) {
        const uint32_t v = ((i & 63) < 8) ? 0x3F803F80u : 0u;
        *(uint4*)(smem + K1_X + (i >> 6) * K1_XB + 16384 + (i & 63) * 16) = make_uint4(v, v, v, v);
    }
    fence_async_smem();
    named_bar(1, 384);
    float acc[68];
    const int tok = tid & 127;
    float shift = 0.f, s1[2] = {0.f, 0.f}, s2[2] = {0.f, 0.f};
    {
        uint64_t da = make_desc(sb + K1_W + wg * 8192, 16, 1024, 1), db = make_desc(sb + K1_X, 16, 1024, 1);
        int st = 0, ph = 0, pst = 0;
#pragma unroll kK1Unroll
        for (int kb = 0; kb < 8; kb++) {
            mbar_wait(bar_x + 8 * kb, 0);
            mbar_wait(bar_full + 8 * st, ph);
            WG_FENCE();
#pragma unroll
            for (int k = 0; k < 4; k++) {
                wgmma_n136_ta(acc, da, db, kb | k);
                if (k < 3) DESC_ADV(da, 128); else DESC_ADV(da, st < K1_NST - 1 ? (K1_STAGE >> 4) - 384 : -((K1_NST - 1) * (K1_STAGE >> 4) + 384));
                DESC_ADV(db, k < 3 ? 2 : (K1_XB >> 4) - 6);
            }
            WG_COMMIT();
            if (kb > 0 && kb < 8 - K1_NST + 1) {
                WG_WAIT(1);
                if (lane == 0) mbar_arrive(bar_empty + 8 * pst);
            }
            pst = st;
            if (++st == K1_NST) { st = 0; ph ^= 1; }
            if (kb == 0) shift = bf_lo(*(const uint32_t*)(smem + K1_X + tok * 128 + ((tok & 7) << 4)));
            {
                const uint8_t* row = smem + K1_X + kb * K1_XB + tok * 128;
#pragma unroll
                for (int i = 0; i < 3; i++) {
                    const int c = wg * 3 + i;
                    if (i < 2 || wg < 2) {
                        const uint4 v = *(const uint4*)(row + ((c ^ (tok & 7)) << 4));
                        const uint32_t vv[4] = {v.x, v.y, v.z, v.w};
#pragma unroll
                        for (int e = 0; e < 4; e++) {
                            const float a = bf_lo(vv[e]) - shift, b = bf_hi(vv[e]) - shift;
                            s1[e & 1] += a + b;
                            s2[e & 1] = fmaf(a, a, fmaf(b, b, s2[e & 1]));
                        }
                    }
                }
            }
        }
        if (tid == 0) TS(0, 0);
        *(float2*)(smem + K1_PART + (wg * 128 + tok) * 8) = make_float2(s1[0] + s1[1], s2[0] + s2[1]);
        named_bar(1, 384);
        if (wg == 0) {
            const float2 p0 = *(const float2*)(smem + K1_PART + tok * 8), p1 = *(const float2*)(smem + K1_PART + (128 + tok) * 8),
                         p2 = *(const float2*)(smem + K1_PART + (256 + tok) * 8);
            const float m = (p0.x + p1.x + p2.x) * (1.f / D);
            const float var = fmaxf((p0.y + p1.y + p2.y) * (1.f / D) - m * m, 0.f);
            *(float2*)(smem + K1_TAB + tok * 8) = make_float2(shift + m, rsqrtf(var + 1e-5f));
        }
        named_bar(1, 384);
        {
            for (int r = ct * 16 + warp; r < ct * 16 + 16; r += 12) {
                const float2 st = *(const float2*)(smem + K1_TAB + r * 8);
                const uint8_t* p = smem + K1_X + (lane >> 3) * K1_XB + r * 128 + (((lane & 7) ^ (r & 7)) << 4);
                uint4* g = (uint4*)(g_xn + (size_t)(rt * 128 + r) * D);
#pragma unroll
                for (int hh = 0; hh < 2; hh++) {
                    const uint4 v = *(const uint4*)(p + hh * 4 * K1_XB);
                    uint4 o;
                    o.x = pack2((bf_lo(v.x) - st.x) * st.y, (bf_hi(v.x) - st.x) * st.y);
                    o.y = pack2((bf_lo(v.y) - st.x) * st.y, (bf_hi(v.y) - st.x) * st.y);
                    o.z = pack2((bf_lo(v.z) - st.x) * st.y, (bf_hi(v.z) - st.x) * st.y);
                    o.w = pack2((bf_lo(v.w) - st.x) * st.y, (bf_hi(v.w) - st.x) * st.y);
                    g[hh * 32 + lane] = o;
                }
            }
        }
        WG_WAIT(0);
        keep(acc);
        named_bar(1, 384);
        if (tid == 0) TS(0, 1);
    }
    if (tid == 0) TS(0, 3);
    {
        const int col = ct * 192 + wg * 64 + w * 16;
        const int which = col >> 9, head = (col >> 4) & 31, t = lane & 3;
        const float sc = which == 0 ? Q_SCALE : 1.f;
        const float cs0 = __shfl_sync(~0u, acc[64], lane & ~3), cs1 = __shfl_sync(~0u, acc[66], lane & ~3);
        const uint32_t stg = sb + K1_W + warp * 4096;
#pragma unroll
        for (int jp = 0; jp < 8; jp++) {
            uint32_t r[4];
#pragma unroll
            for (int jj = 0; jj < 2; jj++) {
                const int j = 2 * jp + jj;
                const float4 st = *(const float4*)(smem + K1_TAB + (8 * j + 2 * t) * 8);
                const float a0 = st.y * sc, a1 = st.w * sc;
                r[2 * jj] = pack2(fmaf(-st.x, cs0, acc[4 * j]) * a0, fmaf(-st.z, cs0, acc[4 * j + 1]) * a1);
                r[2 * jj + 1] = pack2(fmaf(-st.x, cs1, acc[4 * j + 2]) * a0, fmaf(-st.z, cs1, acc[4 * j + 3]) * a1);
            }
            const int mi = lane >> 3;
            stsm_x4_t(stg + (mi & 1) * 2048 + (8 * (2 * jp + (mi >> 1)) + (lane & 7)) * 16, r[0], r[1], r[2], r[3]);
        }
        if (tid == 0) TS(0, 4);
        __syncwarp();
        uint4* dst;
        int pitch;
        if (which == 0) { dst = g_q + head * 2 * S + rt * 128; pitch = S; }
        else { dst = g_kv + ((head * 16 + rt) * 4 + (which - 1) * 2) * 128; pitch = 128; }
        const uint4* src = (const uint4*)(smem + K1_W + warp * 4096);
#pragma unroll
        for (int i = 0; i < 8; i++) dst[(i >> 2) * pitch + (i & 3) * 32 + lane] = src[i * 32 + lane];
        if (tid == 0) TS(0, 5);
    }
    if (tid == 0) TS(0, 2);
    if (tid == 0) GT(0, 1);
}

constexpr int K2_WNST = 2;
constexpr int K2_X = 0, K2_W = 131072, K2_XCH = K2_W + K2_WNST * 16384, K2_RING = K2_XCH + 8192, K2_RSTAGE = 10240, K2_RNST = 4;
constexpr int K2_BAR = K2_RING + K2_RNST * K2_RSTAGE, K2_SMEM = K2_BAR + 512;
constexpr int K2_DSTAGE = 24576, K2_DNST = 4;
constexpr int K2_THREADS = 640;
#define FFN_BATCH 4

#define POLL_NS 100
#define ATT_ALT 0
#define POLY_MASK 0xDADA
#define REFOFF 80.f
constexpr float REF_OFFSET = REFOFF;
constexpr float POLY_LOG2K = -0.052214f;

struct PolyC { uint32_t one, e2; };
__device__ __forceinline__ uint32_t exp2_soft(float a, float b, float bz, const PolyC& c) {
    float ra, rb;
    asm("fma.rn.sat.f32 %0, %1, 0f00000080, %2;" : "=f"(ra) : "f"(a), "f"(bz));
    asm("fma.rn.sat.f32 %0, %1, 0f00000080, %2;" : "=f"(rb) : "f"(b), "f"(bz));
    uint32_t W, G, d, Y;
    asm("cvt.pack.sat.s16.s32 %0, %1, %2;" : "=r"(W) : "r"(__float_as_uint(rb)), "r"(__float_as_uint(ra)));
    asm("lop3.b32 %0, %1, 0x007F007F, %2, 0xEA;" : "=r"(G) : "r"(W), "r"(c.one));
    asm("fma.rn.bf16x2 %0, %1, %2, %3;" : "=r"(d) : "r"(G), "r"(c.e2), "r"(0xBF27BF27u));
    asm("fma.rn.bf16x2 %0, %1, %2, %3;" : "=r"(d) : "r"(G), "r"(d), "r"(0x3EC83EC8u));
    asm("fma.rn.bf16x2 %0, %1, %2, %1;" : "=r"(Y) : "r"(W), "r"(d));
    return Y;
}
__device__ __forceinline__ void softmax_step(const float (&s)[32], uint32_t (&p)[16], float nm0, float nm1, float bz0, float bz1, const PolyC& c) {
#pragma unroll
    for (int i = 0; i < 16; i++)
        if (!((POLY_MASK >> i) & 1)) { const float nm = (i & 1) ? nm1 : nm0; p[i] = pack2(ex2(s[2 * i] + nm), ex2(s[2 * i + 1] + nm)); }
#pragma unroll
    for (int i = 0; i < 16; i++)
        if ((POLY_MASK >> i) & 1) p[i] = exp2_soft(s[2 * i], s[2 * i + 1], (i & 1) ? bz1 : bz0, c);
}
template <int MASK>
__device__ __forceinline__ void softmax_half(const float (&s)[16], uint32_t (&p)[8], float nm0, float nm1, float bz0, float bz1, const PolyC& c) {
#pragma unroll
    for (int i = 0; i < 8; i++)
        if (!((MASK >> i) & 1)) { const float nm = (i & 1) ? nm1 : nm0; p[i] = pack2(ex2(s[2 * i] + nm), ex2(s[2 * i + 1] + nm)); }
#pragma unroll
    for (int i = 0; i < 8; i++)
        if ((MASK >> i) & 1) p[i] = exp2_soft(s[2 * i], s[2 * i + 1], (i & 1) ? bz1 : bz0, c);
}
template <int N> __device__ __forceinline__ void keepr(uint32_t (&a)[N]) {
#pragma unroll
    for (int i = 0; i < N; i++) asm volatile("" : "+r"(a[i])::"memory");
}
__device__ __forceinline__ void mma16816(float (&d)[4], const uint32_t* a, uint32_t b0, uint32_t b1) {
    asm volatile("mma.sync.aligned.m16n8k16.row.col.f32.bf16.bf16.f32 {%0,%1,%2,%3},{%4,%5,%6,%7},{%8,%9},{%0,%1,%2,%3};"
                 : "+f"(d[0]), "+f"(d[1]), "+f"(d[2]), "+f"(d[3]) : "r"(a[0]), "r"(a[1]), "r"(a[2]), "r"(a[3]), "r"(b0), "r"(b1));
}
__device__ __forceinline__ void attn_rows_true_max(const uint32_t (&qf)[4], const uint4* gkv, __nv_bfloat16* orow, int lane) {
    const int g = lane >> 2, t = lane & 3;
    auto row = [&](int plane, int key) { return gkv + ((key >> 7) * 4 + plane) * 128 + (key & 127); };
    auto kw = [&](int plane, int key) { return ((const uint32_t*)row(plane, key))[t]; };
    auto vw = [&](int plane, int key) { return ((const uint16_t*)row(plane, key))[g] | ((uint32_t)((const uint16_t*)row(plane, key + 1))[g] << 16); };
    float m0 = -INFINITY, m1 = -INFINITY;
#pragma unroll 1
    for (int kb = 0; kb < S / 8; kb++) {
        float s[4] = {0.f, 0.f, 0.f, 0.f};
        mma16816(s, qf, kw(0, kb * 8 + g), kw(1, kb * 8 + g));
        m0 = fmaxf(m0, fmaxf(s[0], s[1]));
        m1 = fmaxf(m1, fmaxf(s[2], s[3]));
    }
    m0 = fmaxf(m0, __shfl_xor_sync(~0u, m0, 1)); m0 = fmaxf(m0, __shfl_xor_sync(~0u, m0, 2));
    m1 = fmaxf(m1, __shfl_xor_sync(~0u, m1, 1)); m1 = fmaxf(m1, __shfl_xor_sync(~0u, m1, 2));
    float o0[4] = {0.f, 0.f, 0.f, 0.f}, o1[4] = {0.f, 0.f, 0.f, 0.f}, l0 = 0.f, l1 = 0.f;
#pragma unroll 1
    for (int kb = 0; kb < S / 16; kb++) {
        float sa[4] = {0.f, 0.f, 0.f, 0.f}, sc[4] = {0.f, 0.f, 0.f, 0.f};
        mma16816(sa, qf, kw(0, kb * 16 + g), kw(1, kb * 16 + g));
        mma16816(sc, qf, kw(0, kb * 16 + 8 + g), kw(1, kb * 16 + 8 + g));
        uint32_t p[4];
        p[0] = pack2(ex2(sa[0] - m0), ex2(sa[1] - m0));
        p[1] = pack2(ex2(sa[2] - m1), ex2(sa[3] - m1));
        p[2] = pack2(ex2(sc[0] - m0), ex2(sc[1] - m0));
        p[3] = pack2(ex2(sc[2] - m1), ex2(sc[3] - m1));
        l0 += bf_lo(p[0]) + bf_hi(p[0]) + bf_lo(p[2]) + bf_hi(p[2]);
        l1 += bf_lo(p[1]) + bf_hi(p[1]) + bf_lo(p[3]) + bf_hi(p[3]);
        const int key = kb * 16 + 2 * t;
        mma16816(o0, p, vw(2, key), vw(2, key + 8));
        mma16816(o1, p, vw(3, key), vw(3, key + 8));
    }
    l0 += __shfl_xor_sync(~0u, l0, 1); l0 += __shfl_xor_sync(~0u, l0, 2);
    l1 += __shfl_xor_sync(~0u, l1, 1); l1 += __shfl_xor_sync(~0u, l1, 2);
    const float i0 = 1.f / l0, i1 = 1.f / l1;
    *(uint32_t*)(orow + 2 * t) = pack2(o0[0] * i0, o0[1] * i0);
    *(uint32_t*)(orow + 8 + 2 * t) = pack2(o1[0] * i0, o1[1] * i0);
    *(uint32_t*)(orow + 8 * D + 2 * t) = pack2(o0[2] * i1, o0[3] * i1);
    *(uint32_t*)(orow + 8 * D + 8 + 2 * t) = pack2(o1[2] * i1, o1[3] * i1);
}

__global__ void __launch_bounds__(K2_THREADS, 1)
k2_attn_ffn(const __grid_constant__ CUtensorMap tm_xn, const __grid_constant__ CUtensorMap tm_wg, const __grid_constant__ CUtensorMap tm_wu,
            const __grid_constant__ CUtensorMap tm_wd, const __grid_constant__ CUtensorMap tm_h, const __grid_constant__ CUtensorMap tm_o,
            const __grid_constant__ CUtensorMap tm_wo, const __nv_bfloat16* __restrict__ x, __nv_bfloat16* __restrict__ out, uint32_t zero) {
    extern __shared__ __align__(1024) uint8_t smem[];
    const uint32_t sb = smem_u32(smem);
    const uint32_t bar_rfull = sb + K2_BAR, bar_rempty = bar_rfull + 32;
    const uint32_t bar_x = bar_rempty + 32, bar_wfull = bar_x + 64, bar_dfull = bar_wfull + 8 * K2_WNST;
    const uint32_t bar_o = bar_dfull + 8 * K2_DNST, bar_wo = bar_o + 64;
    const int tid = threadIdx.x, lane = tid & 31;
    const int wg = __shfl_sync(~0u, tid >> 7, 0);
    TS_INIT();
    if (tid == 0) GT(1, 0);
    if (tid == 0) {
        for (int i = 0; i < 4; i++) { mbar_init(bar_rfull + 8 * i, 1); mbar_init(bar_rempty + 8 * i, 16); }
        for (int i = 0; i < K2_WNST; i++) mbar_init(bar_wfull + 8 * i, 1);
        for (int i = 0; i < K2_DNST; i++) mbar_init(bar_dfull + 8 * i, 1);
        for (int i = 0; i < 8; i++) { mbar_init(bar_x + 8 * i, 1); mbar_init(bar_o + 8 * i, 1); mbar_init(bar_wo + 8 * i, 1); }
        fence_bar_init();
    }
    if (tid < K2_RNST * 128) *(uint4*)(smem + K2_RING + (tid >> 7) * K2_RSTAGE + 8192 + (tid & 127) * 16) = make_uint4(0x00003F80u, 0, 0, 0);
    fence_async_smem();
    __syncthreads();

    if (wg < 4) {
        pdl_wait();
        if (tid == 0) TS(1, 0);
        if (tid == 0) GT(1, 2);
        const int head = blockIdx.x >> 2, part = blockIdx.x & 3;
        const int warp4 = (tid >> 5) & 3;
        const uint4* gq = g_q + head * 2 * S;
        PolyC pc;
        pc.one = 0x3F803F80u ^ zero;
        pc.e2 = 0x3E623E62u ^ zero;
        const uint64_t dk0 = make_desc(sb + K2_RING, 2048, 128, 0), dv0 = make_desc(sb + K2_RING + 4096, 128, 2048, 0);
        constexpr int RS = K2_RSTAGE >> 4;
        uint32_t qf[4];
        auto load_q = [&](int rnd) {
            const uint32_t* qp = (const uint32_t*)(gq + part * 512 + (rnd * 4 + wg) * 64 + warp4 * 16 + (lane >> 2)) + (lane & 3);
            qf[0] = qp[0]; qf[1] = qp[32]; qf[2] = qp[S * 4]; qf[3] = qp[S * 4 + 32];
        };
        load_q(0);
#pragma unroll 1
        for (int rnd = 0; rnd < 2; rnd++) {
            const int row0 = part * 512 + (rnd * 4 + wg) * 64 + warp4 * 16;
            float s[32], o[12];
            uint32_t p[16];
            mbar_wait(bar_rfull, 0);
            WG_FENCE(); wgmma_qk(s, qf, dk0); WG_COMMIT(); WG_WAIT(0); keep(s);
            if (wg == 0 && rnd == 0) TS(1, 1);
            float m0 = -INFINITY, m1 = -INFINITY;
#pragma unroll
            for (int i = 0; i < 32; i += 4) { m0 = fmaxf(m0, fmaxf(s[i], s[i + 1])); m1 = fmaxf(m1, fmaxf(s[i + 2], s[i + 3])); }
            m0 = fmaxf(m0, __shfl_xor_sync(~0u, m0, 1)); m0 = fmaxf(m0, __shfl_xor_sync(~0u, m0, 2));
            m1 = fmaxf(m1, __shfl_xor_sync(~0u, m1, 1)); m1 = fmaxf(m1, __shfl_xor_sync(~0u, m1, 2));
            m0 = ceilf(m0) + REF_OFFSET; m1 = ceilf(m1) + REF_OFFSET;
            float nm0 = POLY_LOG2K - m0, nm1 = POLY_LOG2K - m1;
            float bz0 = __fmul_rn(__fmul_rn(127.0f - m0, 0x1p-71f), 0x1p-71f), bz1 = __fmul_rn(__fmul_rn(127.0f - m1, 0x1p-71f), 0x1p-71f);
            asm volatile("" : "+f"(nm0), "+f"(nm1), "+f"(bz0), "+f"(bz1));
#pragma unroll
            for (int i = 0; i < 12; i++) o[i] = 0.f;
#pragma unroll 1
            for (int it = 0; it < 8; it++) {
                const int s0 = (it & 1) * 2;
                const uint32_t par = (it >> 1) & 1;
                uint64_t dk = dk0 + s0 * RS, dv = dv0 + s0 * RS;
#pragma unroll
                for (int u = 0; u < 4; u++) {
                    if (u == 0 || u == 2) mbar_wait(bar_rfull + 8 * (s0 + (u >> 1)), par);
                    WG_FENCE(); wgmma_qk(s, qf, dk); WG_COMMIT();
                    if (u == 1) DESC_ADV(dk, 576); else DESC_ADV(dk, 64);
                    WG_WAIT(0); keep(s);
                    if (u == 2 && lane == 0) mbar_arrive(bar_rempty + 8 * s0);
                    if (u == 0 && it > 0 && lane == 0) mbar_arrive(bar_rempty + 8 * ((s0 + 3) & 3));
                    softmax_step(s, p, nm0, nm1, bz0, bz1, pc);
                    WG_FENCE();
                    wgmma_pv(o, p, dv); DESC_ADV(dv, 16);
                    wgmma_pv(o, p + 4, dv); DESC_ADV(dv, 16);
                    wgmma_pv(o, p + 8, dv); DESC_ADV(dv, 16);
                    wgmma_pv(o, p + 12, dv);
                    if (u == 1) DESC_ADV(dv, 528); else DESC_ADV(dv, 16);
                    WG_COMMIT();
                }
            }
            uint32_t qo[4] = {qf[0], qf[1], qf[2], qf[3]};
            if (rnd == 0) load_q(1);
            WG_WAIT(0);
            keep(o);
            if (lane == 0) mbar_arrive(bar_rempty + 8 * 3);
            const float l0 = __shfl_sync(~0u, o[8], lane & ~3), l1 = __shfl_sync(~0u, o[10], lane & ~3);
            bool bad = !(l0 < 0x1p120f) || !(l1 < 0x1p120f);
#pragma unroll
            for (int i = 0; i < 8; i++) bad = bad || !(fabsf(o[i]) < INFINITY);
            __nv_bfloat16* orow = g_o + (size_t)(row0 + (lane >> 2)) * D + head * 16;
            if (__any_sync(~0u, bad)) {
                attn_rows_true_max(qo, g_kv + head * 8192, orow, lane);
            } else {
                const float i0 = rcp(l0), i1 = rcp(l1);
                const int t = lane & 3;
                *(uint32_t*)(orow + 2 * t) = pack2(o[0] * i0, o[1] * i0);
                *(uint32_t*)(orow + 8 + 2 * t) = pack2(o[4] * i0, o[5] * i0);
                *(uint32_t*)(orow + 8 * D + 2 * t) = pack2(o[2] * i1, o[3] * i1);
                *(uint32_t*)(orow + 8 * D + 8 + 2 * t) = pack2(o[6] * i1, o[7] * i1);
            }
            TS(1, 2 + rnd * 4 + wg);
        }
        named_bar(8 + wg, 128);
        if ((tid & 127) == 0) {
            asm volatile("fence.acq_rel.gpu;" ::: "memory");
            asm volatile("red.relaxed.gpu.global.add.u32 [%0], 1;" ::"l"(&g_flag[FLAG_O + (part * 4 + (wg >> 1)) * 8 + (head >> 2)]) : "memory");
            asm volatile("red.relaxed.gpu.global.add.u32 [%0], 1;" ::"l"(&g_flag[FLAG_O + (part * 4 + 2 + (wg >> 1)) * 8 + (head >> 2)]) : "memory");
        }
        if (tid == 0) GT(1, 1);
        const int rt = blockIdx.x >> 3, ct = blockIdx.x & 7;
        const int g = lane >> 2, t = lane & 3;
        const int tok = (wg & 1) * 64 + warp4 * 16 + g;
        const size_t e0 = (size_t)(rt * 128 + tok) * D + ct * 64 + 2 * t;
        uint32_t xv[16];
        if (wg < 2) {
#pragma unroll
            for (int j = 0; j < 8; j++) { xv[2 * j] = *(const uint32_t*)(x + e0 + 8 * j); xv[2 * j + 1] = *(const uint32_t*)(x + e0 + 8 * D + 8 * j); }
        }
        named_bar(12, K2_THREADS);
        if (tid == 0) GT(2, 0);
        if (wg == 2 && warp4 == 0) {
            if (elect_one())
                for (int kb = 3; kb < 8; kb++) { mbar_expect(bar_wo + 8 * kb, 8192); tma_load(sb + K2_RING + (kb - 3) * 8192, &tm_wo, ct * 64, kb * 64, bar_wo + 8 * kb); }
        } else if (wg == 3 && warp4 == 0) {
            uint32_t pending = 0xFF;
            int slot = 0, spin = 0;
            while (pending) {
                unsigned v = 0;
                if (lane < 8) asm volatile("ld.acquire.gpu.global.u32 %0, [%1];" : "=r"(v) : "l"(&g_flag[FLAG_O + rt * 8 + lane]) : "memory");
                uint32_t ready = __ballot_sync(~0u, v >= 8) & pending;
                pending &= ~ready;
                if (ready) asm volatile("fence.proxy.async.global;" ::: "memory");
                else __nanosleep(POLL_NS);
                while (ready) {
                    const int kb = __ffs(ready) - 1;
                    ready &= ready - 1;
                    if (elect_one()) {
                        *(volatile int*)(smem + K2_BAR + 384 + 4 * slot) = kb;
                        mbar_expect(bar_o + 8 * slot, 16384);
                        tma_load(sb + K2_X + kb * 16384, &tm_o, kb * 64, rt * 128, bar_o + 8 * slot);
                    }
                    slot++;
                }
                if (++spin > (1 << 22)) __trap();
            }
        } else if (wg < 2) {
            float acc[32];
            const uint64_t da0 = make_desc(sb + K2_X + wg * 8192, 16, 1024, 1);
#pragma unroll 1
            for (int slot = 0; slot < 8; slot++) {
                mbar_wait(bar_o + 8 * slot, 0);
                const int kb = __shfl_sync(~0u, *(volatile const int*)(smem + K2_BAR + 384 + 4 * slot), 0);
                if (tid == 0 && slot == 0) GT(2, 2);
                if (tid == 0 && slot == 7) GT(2, 3);
                const uint32_t wo_addr = kb < 2 ? sb + K2_W + 16384 + kb * 8192 : (kb == 2 ? sb + K2_XCH : sb + K2_RING + (kb - 3) * 8192);
                const uint64_t da = da0 + kb * 1024, db = make_desc(wo_addr, 16, 1024, 1);
                mbar_wait(bar_wo + 8 * kb, 0);
                WG_FENCE();
#pragma unroll
                for (int k = 0; k < 4; k++) wgmma_n64_tb(acc, da + k * 2, db + k * 128, slot | k);
                WG_COMMIT();
            }
            WG_WAIT(0);
            keep(acc);
#pragma unroll
            for (int j = 0; j < 8; j++) {
                const uint8_t* gp = smem + K2_W + tok * 128 + 4 * t;
                const uint32_t g0 = *(const uint32_t*)(gp + ((j ^ (tok & 7)) << 4)), g1 = *(const uint32_t*)(gp + 1024 + ((j ^ (tok & 7)) << 4));
                *(uint32_t*)(out + e0 + 8 * j) = pack2(fmaf(acc[4 * j], bf_lo(g0), bf_lo(xv[2 * j])), fmaf(acc[4 * j + 1], bf_hi(g0), bf_hi(xv[2 * j])));
                *(uint32_t*)(out + e0 + 8 * D + 8 * j) =
                    pack2(fmaf(acc[4 * j + 2], bf_lo(g1), bf_lo(xv[2 * j + 1])), fmaf(acc[4 * j + 3], bf_hi(g1), bf_hi(xv[2 * j + 1])));
            }
            if (tid == 0) GT(2, 1);
        }
    } else {
        const int rt = blockIdx.x >> 3, ct = blockIdx.x & 7;
        const int w = __shfl_sync(~0u, (tid >> 5) & 3, 0);
        float acc[64];
        const uint4* gkv = g_kv + (blockIdx.x >> 2) * 8192;
        int rn = 0;
        auto ring_issue = [&]() {
            if (elect_one()) {
                mbar_expect(bar_rfull + 8 * (rn & 3), 8192);
                bulk_load(sb + K2_RING + (rn & 3) * K2_RSTAGE, gkv + (rn & 15) * 512, 8192, bar_rfull + 8 * (rn & 3));
            }
            rn++;
        };
        auto ring_ready = [&]() { return mbar_test(bar_rempty + 8 * (rn & 3), ((rn >> 2) & 1) ^ 1); };
        auto ring_poll = [&]() { if (w == 1 && rn < 32 && ring_ready()) ring_issue(); };
        auto ring_drain = [&]() { if (w == 1) while (rn < 32) { mbar_wait(bar_rempty + 8 * (rn & 3), ((rn >> 2) & 1) ^ 1); ring_issue(); } };
        auto load_w = [&](int n, int stage) {
            if (elect_one()) {
                const int col = ct * 224 + (n >> 2) * 32, k = (n & 3) * 128;
                mbar_expect(bar_wfull + 8 * stage, 16384);
                tma_load(sb + K2_W + stage * 16384, &tm_wg, col, k, bar_wfull + 8 * stage);
                tma_load(sb + K2_W + stage * 16384 + 8192, &tm_wu, col, k, bar_wfull + 8 * stage);
            }
        };
        auto released = [&](int id) { if (w == 0) named_bar(id, 128); else named_arrive(id, 128); };
        if (w == 0) { load_w(0, 0); load_w(1, 1); }
        pdl_wait();
        if (w == 1) { ring_issue(); ring_issue(); ring_issue(); ring_issue(); }
        if (w == 0 && elect_one()) {
            for (int kb = 0; kb < 8; kb++) { mbar_expect(bar_x + 8 * kb, 16384); tma_load(sb + K2_X + kb * 16384, &tm_xn, kb * 64, rt * 128, bar_x + 8 * kb); }
        }
        {
            uint64_t da = make_desc(sb + K2_W, 8192, 512, 2), db = make_desc(sb + K2_X, 16, 1024, 1);
            uint32_t mine[16];
            auto finish_tile = [&](int tile) {
                named_bar(2, 128);
                if (tile == 4 && w == 3 && lane == 0) flag_publish(FLAG_H + rt * 2);
                const uint4* xr = (const uint4*)(smem + K2_XCH) + (w ^ 2) * 128 + lane;
#pragma unroll
                for (int i = 0; i < 4; i++) {
                    const uint4 r = xr[i * 32];
                    const uint32_t rr[4] = {r.x, r.y, r.z, r.w};
#pragma unroll
                    for (int e = 0; e < 4; e++) asm("mul.rn.bf16x2 %0, %0, %1;" : "+r"(mine[4 * i + e]) : "r"(rr[e]));
                }
                const int g = lane >> 2, t = lane & 3, odd = t & 1;
                __nv_bfloat16* hrow = g_h + (size_t)(ct * 224 + tile * 32 + (w & 1) * 16 + g) * S + rt * 128 + (w >> 1) * 64 + odd * 8 + (t >> 1) * 4;
#pragma unroll
                for (int jp = 0; jp < 4; jp++)
#pragma unroll
                    for (int r = 0; r < 2; r++) {
                        const uint32_t a = mine[4 * jp + r], b = mine[4 * jp + 2 + r];
                        const uint32_t got = __shfl_xor_sync(~0u, odd ? a : b, 1);
                        *(uint2*)(hrow + (size_t)r * 8 * S + jp * 16) = odd ? make_uint2(got, b) : make_uint2(a, got);
                    }
            };
#pragma unroll 1
            for (int tile = 0; tile < 7; tile++) {
#pragma unroll
                for (int kd = 0; kd < 4; kd++) {
                    if (tile == 0) { mbar_wait(bar_x + 16 * kd, 0); mbar_wait(bar_x + 16 * kd + 8, 0); }
                    mbar_wait(bar_wfull + 8 * (kd & 1), kd >> 1);
                    WG_FENCE();
#pragma unroll
                    for (int k = 0; k < 8; k++) {
                        wgmma_n128_ta(acc, da, db, kd | k);
                        DESC_ADV(da, k < 7 ? 64 : ((kd & 1) == 0 ? 1024 - 448 : -(1024 + 448)));
                        DESC_ADV(db, (k & 3) < 3 ? 2 : (k == 3 || kd < 3 ? 1024 - 6 : -(7 * 1024 + 6)));
                        if (k == 1 && kd > 0) {
                            WG_COMMIT();
                            WG_WAIT(1);
                            released(3 + (kd & 1));
                            if (w == 0 && (kd < 3 || tile < 6)) load_w(tile * 4 + kd + 1, (kd - 1) & 1);
                            WG_FENCE();
                        }
                    }
                    WG_COMMIT();
                    if (kd == 0 && tile > 0) finish_tile(tile - 1);
                    ring_poll();
                }
                WG_WAIT(0);
                released(3);
                if (w == 0 && tile < 6) load_w(tile * 4 + 5, 1);
                keep(acc);
                uint4* xs = (uint4*)(smem + K2_XCH) + w * 128 + lane;
                if (w < 2) {
#pragma unroll
                    for (int i = 0; i < 16; i++) mine[i] = pack2(acc[2 * i], acc[2 * i + 1]);
#pragma unroll
                    for (int i = 0; i < 4; i++)
                        xs[i * 32] = make_uint4(pack2(acc[32 + 8 * i], acc[33 + 8 * i]), pack2(acc[34 + 8 * i], acc[35 + 8 * i]),
                                                pack2(acc[36 + 8 * i], acc[37 + 8 * i]), pack2(acc[38 + 8 * i], acc[39 + 8 * i]));
                } else {
#pragma unroll
                    for (int i = 0; i < 16; i++) mine[i] = pack2(acc[32 + 2 * i], acc[33 + 2 * i]);
#pragma unroll
                    for (int i = 0; i < 4; i++)
                        xs[i * 32] = make_uint4(pack2(acc[8 * i], acc[1 + 8 * i]), pack2(acc[2 + 8 * i], acc[3 + 8 * i]),
                                                pack2(acc[4 + 8 * i], acc[5 + 8 * i]), pack2(acc[6 + 8 * i], acc[7 + 8 * i]));
                }
            }
            finish_tile(6);
        }
        TS(1, 10);
        named_bar(2, 128);
        if (w == 3 && lane == 0) flag_publish(FLAG_H + rt * 2 + 1);
        auto wait_flag = [&](int which) {
            if (lane == 0) flag_wait(FLAG_H + rt * 2 + which, 8);
            __syncwarp();
            asm volatile("fence.proxy.async.global;" ::: "memory");
        };
        auto load_d = [&](int i, int stage) {
            if (i == 0) wait_flag(0);
            if (i == 12) wait_flag(1);
            if (elect_one()) {
                const int j = (i < 12) ? 7 * (i / 3) + ((0x410 >> (4 * (i % 3))) & 7) : 7 * ((i - 12) >> 2) + ((0x6532 >> (4 * ((i - 12) & 3))) & 7);
                const uint32_t dst = sb + K2_X + stage * K2_DSTAGE;
                mbar_expect(bar_dfull + 8 * stage, K2_DSTAGE);
                tma_load(dst, &tm_wd, ct * 64, j * 64, bar_dfull + 8 * stage);
                tma_load(dst + 8192, &tm_h, rt * 128, j * 64, bar_dfull + 8 * stage);
                tma_load(dst + 16384, &tm_h, rt * 128 + 64, j * 64, bar_dfull + 8 * stage);
            }
        };
        if (w == 0) { load_d(0, 0); load_d(1, 1); load_d(2, 2); load_d(3, 3); }
        if (w == 2 && elect_one()) {
            for (int kb = 0; kb < 3; kb++) {
                mbar_expect(bar_wo + 8 * kb, 8192);
                tma_load(kb < 2 ? sb + K2_W + 16384 + kb * 8192 : sb + K2_XCH, &tm_wo, ct * 64, kb * 64, bar_wo + 8 * kb);
            }
        }
        {
            uint64_t da = make_desc(sb + K2_X, 16, 1024, 1), db = make_desc(sb + K2_X + 8192, 8192, 1024, 1);
            {
                int spin = 0;
                while (!mbar_test(bar_dfull, 0)) { ring_poll(); if (++spin > (1 << 26)) __trap(); }
            }
            TS(1, 11);
#pragma unroll 1
            for (int it = 0; it < 7; it++) {
#pragma unroll
                for (int q = 0; q < 4; q++) {
                    constexpr int DS = K2_DSTAGE >> 4;
                    mbar_wait(bar_dfull + 8 * q, it & 1);
                    WG_FENCE();
#pragma unroll
                    for (int k = 0; k < 4; k++) {
                        wgmma_n128_tab(acc, da, db, it | q | k);
                        const int adv = k < 3 ? 128 : (q < 3 ? DS - 384 : -(3 * DS + 384));
                        DESC_ADV(da, adv); DESC_ADV(db, adv);
                        if (k == 1 && (q > 0 || it > 0)) {
                            WG_COMMIT();
                            WG_WAIT(1);
                            released(3 + (q & 1));
                            const int n = it * 4 + q + 3;
                            if (w == 0 && n < 28) load_d(n, (q + 3) & 3);
                            WG_FENCE();
                        }
                    }
                    WG_COMMIT();
                    if (q & 1) ring_poll();
                }
            }
            WG_WAIT(0);
            keep(acc);
            TS(1, 12);
#pragma unroll
            for (int i = 0; i < 8; i++) {
                uint32_t gv[4];
#pragma unroll
                for (int e = 0; e < 4; e++) {
                    const float y0 = acc[8 * i + 2 * e], y1 = acc[8 * i + 2 * e + 1];
                    gv[e] = pack2(__fdividef(y0, 1.f + __expf(-y0)), __fdividef(y1, 1.f + __expf(-y1)));
                }
                const int mi = lane >> 3;
                const int tok = 8 * (2 * i + (mi >> 1)) + (lane & 7);
                const int chunk = 2 * w + (mi & 1);
                stsm_x4_t(sb + K2_W + tok * 128 + ((chunk ^ (tok & 7)) << 4), gv[0], gv[1], gv[2], gv[3]);
            }
            TS(1, 13);
            if (tid == 512) GT(1, 3);
        }
        ring_drain();
        named_bar(12, K2_THREADS);
    }
}

typedef CUresult (*EncodeFn)(CUtensorMap*, CUtensorMapDataType, cuuint32_t, void*, const cuuint64_t*, const cuuint64_t*, const cuuint32_t*,
                             const cuuint32_t*, CUtensorMapInterleave, CUtensorMapSwizzle, CUtensorMapL2promotion, CUtensorMapFloatOOBfill);

CUtensorMap make_map(EncodeFn fn, const void* ptr, int rows, int cols, int box_rows, int box_cols, CUtensorMapSwizzle swz) {
    CUtensorMap m;
    const cuuint64_t dims[2] = {(cuuint64_t)cols, (cuuint64_t)rows};
    const cuuint64_t strides[1] = {(cuuint64_t)cols * 2};
    const cuuint32_t box[2] = {(cuuint32_t)box_cols, (cuuint32_t)box_rows};
    const cuuint32_t estr[2] = {1, 1};
    fn(&m, CU_TENSOR_MAP_DATA_TYPE_BFLOAT16, 2, const_cast<void*>(ptr), dims, strides, box, estr, CU_TENSOR_MAP_INTERLEAVE_NONE, swz,
       CU_TENSOR_MAP_L2_PROMOTION_L2_256B, CU_TENSOR_MAP_FLOAT_OOB_FILL_NONE);
    return m;
}

template <typename... KArgs, typename... Args>
void launch(void (*kern)(KArgs...), int grid, int block, int smem, bool pdl, Args... args) {
    cudaLaunchConfig_t cfg = {};
    cfg.gridDim = dim3(grid);
    cfg.blockDim = dim3(block);
    cfg.dynamicSmemBytes = smem;
    cfg.stream = cudaStreamPerThread;
    cudaLaunchAttribute at[1];
    at[0].id = cudaLaunchAttributeProgrammaticStreamSerialization;
    at[0].val.programmaticStreamSerializationAllowed = 1;
    cfg.attrs = at;
    cfg.numAttrs = pdl ? 1 : 0;
    cudaLaunchKernelEx(&cfg, kern, KArgs(args)...);
}

}

extern "C" void kernel_launch(void* const* d_in, const int* in_sizes, int n_in, void* d_out, int out_size) {
    (void)in_sizes; (void)n_in; (void)out_size;
    const __nv_bfloat16* x = (const __nv_bfloat16*)d_in[0];
    const void* wqkv = d_in[1];
    const void* wo = d_in[2];
    const void* wgate = d_in[4];
    const void* wup = d_in[5];
    const void* wdown = d_in[6];

    static EncodeFn encode = nullptr;
    static void *p_xn, *p_h, *p_o;
    if (!encode) {
        void* fn = nullptr;
        cudaDriverEntryPointQueryResult qr;
        cudaGetDriverEntryPoint("cuTensorMapEncodeTiled", &fn, cudaEnableDefault, &qr);
        encode = (EncodeFn)fn;
        cudaGetSymbolAddress(&p_xn, g_xn);
        cudaGetSymbolAddress(&p_h, g_h);
        cudaGetSymbolAddress(&p_o, g_o);
        cudaFuncSetAttribute(k1_ln_qkv, cudaFuncAttributeMaxDynamicSharedMemorySize, K1_SMEM);
        cudaFuncSetAttribute(k2_attn_ffn, cudaFuncAttributeMaxDynamicSharedMemorySize, K2_SMEM);
    }
    const CUtensorMapSwizzle S128 = CU_TENSOR_MAP_SWIZZLE_128B, S64 = CU_TENSOR_MAP_SWIZZLE_64B;
    const CUtensorMap tm_x = make_map(encode, x, S, D, 128, 64, S128);
    const CUtensorMap tm_wqkv = make_map(encode, wqkv, D, 3 * D, 64, 64, S128);
    const CUtensorMap tm_xn = make_map(encode, p_xn, S, D, 128, 64, S128);
    const CUtensorMap tm_wg = make_map(encode, wgate, D, F, 128, 32, S64);
    const CUtensorMap tm_wu = make_map(encode, wup, D, F, 128, 32, S64);
    const CUtensorMap tm_wd = make_map(encode, wdown, F, D, 64, 64, S128);
    const CUtensorMap tm_h = make_map(encode, p_h, F, S, 64, 64, S128);
    const CUtensorMap tm_o = make_map(encode, p_o, S, D, 128, 64, S128);
    const CUtensorMap tm_wo = make_map(encode, wo, D, D, 64, 64, S128);

    launch(k1_ln_qkv, 128, 416, K1_SMEM, false, tm_x, tm_wqkv, (const uint8_t*)x, (const uint8_t*)wqkv, (const uint8_t*)wgate, (const uint8_t*)wup, (const uint8_t*)wdown, (const uint8_t*)wo);
    launch(k2_attn_ffn, 128, K2_THREADS, K2_SMEM, true, tm_xn, tm_wg, tm_wu, tm_wd, tm_h, tm_o, tm_wo, x, (__nv_bfloat16*)d_out, 0u);
}
```
